```python
import torch

def _softmax(x, axis=-1):
    return torch.softmax(x, dim=axis)
def _gelu(x):
    return torch.nn.functional.gelu(x, approximate="tanh")
def _silu(x):
    return torch.nn.functional.silu(x)
def _sigmoid(x):
    return torch.sigmoid(x)
def _layernorm(x, axis=-1, eps=1e-5):
    m = x.mean(dim=axis, keepdim=True)
    v = x.var(dim=axis, keepdim=True, unbiased=False)
    return (x - m) / torch.sqrt(v + eps)
def _scatter_add(tgt, idx, src, axis=0):
    return tgt.clone().index_add_(axis, idx, src)
def _segment_sum(src, seg, n):
    out = torch.zeros((n,) + src.shape[1:], dtype=src.dtype)
    return out.index_add_(0, seg, src)
def _pad(x, pw):
    flat = tuple(v for pair in reversed(pw) for v in pair)
    return torch.nn.functional.pad(x, flat)

kernel_name = 'sequential_preLN__mha_block_cached__glu_gated_swiglu__decode'

def setup_inputs():

    _w = (lambda a: (lambda t: t.to(torch.bfloat16) if t.is_floating_point() else t)(torch.as_tensor(a)))
    def _A_setup():
        B, Sq, D = 4, 1, 512
        H, Sk, Dh = 32, 4096, 128
        return {
            "x": _w((lambda *s: torch.randn(*s, dtype=torch.bfloat16) * 0.05)(B, Sq, D)),
            "k_cache": _w((lambda *s: torch.randn(*s, dtype=torch.bfloat16) * 1.6)(B, H, Sk, Dh)),
            "v_cache": _w((lambda *s: torch.randn(*s, dtype=torch.bfloat16) * 0.8)(B, H, Sk, Dh)),
            "wq": _w((lambda *s: torch.randn(*s, dtype=torch.bfloat16) * 1.6)(D, H * Dh) * (D ** -0.5)),
            "wo": _w((lambda *s: torch.randn(*s, dtype=torch.bfloat16) * 0.8)(H * Dh, D) * ((H * Dh) ** -0.5)),
        }
    _A_in = _A_setup()

    def _B_setup():
        B, S, D, F = 4, 1, 512, 1792
        return {
            "x": _w((lambda *s: torch.randn(*s, dtype=torch.bfloat16) * 0.05)(B, S, D)),
            "w1": _w((lambda *s: torch.randn(*s, dtype=torch.bfloat16) * 0.4)(D, F) * (2.0 / D) ** 0.5),
            "w3": _w((lambda *s: torch.randn(*s, dtype=torch.bfloat16) * 0.4)(D, F) * (2.0 / D) ** 0.5),
            "w2": _w((lambda *s: torch.randn(*s, dtype=torch.bfloat16) * 0.4)(F, D) * (2.0 / F) ** 0.5),
        }
    _B_in = _B_setup()

    return {
        "A_x": _A_in["x"],
        "A_k_cache": _A_in["k_cache"],
        "A_v_cache": _A_in["v_cache"],
        "A_wq": _A_in["wq"],
        "A_wo": _A_in["wo"],
        "B_x": _B_in["x"],
        "B_w1": _B_in["w1"],
        "B_w3": _B_in["w3"],
        "B_w2": _B_in["w2"],
    }

def reference(A_x, A_k_cache, A_v_cache, A_wq, A_wo, B_x, B_w1, B_w3, B_w2):
    def _A_ref(x, k_cache, v_cache, wq, wo):
        B, Sq, D = x.shape
        H, Dh = 32, 128
        q = (lambda x, *d: x.permute(*d))((x @ wq).reshape(B, Sq, H, Dh), 0, 2, 1, 3)
        scores = torch.einsum("bhqd,bhkd->bhqk", q, k_cache) * (Dh ** -0.5)
        p = _softmax(scores, axis=-1)
        o = torch.einsum("bhqk,bhkd->bhqd", p, v_cache)
        return (lambda x, *d: x.permute(*d))(o, 0, 2, 1, 3).reshape(B, Sq, H * Dh) @ wo

    def _B_ref(x, w1, w3, w2):
        gate = torch.einsum("bsd,df->bsf", x, w1)
        up = torch.einsum("bsd,df->bsf", x, w3)
        h = _silu(gate) * up
        out = torch.einsum("bsf,fd->bsd", h, w2)
        return out

    x = A_x
    h = x + _A_ref(_layernorm(x, axis=-1), A_k_cache, A_v_cache, A_wq, A_wo)
    h2 = h + _B_ref(_layernorm(h, axis=-1), B_w1, B_w3, B_w2)
    return h2
```

```cpp
#include <cuda_runtime.h>
#include <cuda.h>
#include <cuda_bf16.h>
#include <stdint.h>

namespace {

constexpr int kH = 32, kS = 4096, kDH = 128, kD = 512, kF = 1792;
constexpr int NCTA = 128;
constexpr int NFFN = 112;
constexpr int NCW = 16;
constexpr int NCT = NCW * 32;
#define NSTAGE_ 4
#define FFN_PROMO CU_TENSOR_MAP_L2_PROMOTION_L2_64B
#define QFIRST 0
constexpr int TILE_KEYS = 128;
constexpr int TILE_BYTES = TILE_KEYS * kDH * 2;
constexpr int NSTAGE = NSTAGE_;
constexpr int NTILE = kS / TILE_KEYS;
constexpr int NWO = 4;
constexpr int JP = 24;
constexpr int HREP = 4;
constexpr int OP_PITCH = 80;
constexpr uint32_t SPIN_LIMIT = 1u << 19;
static_assert(JP < NTILE - NSTAGE - 1, "prewrite must precede the gate");
static_assert(NSTAGE >= NWO, "ring layout");

struct __align__(1024) Smem {
    uint8_t ring[NSTAGE][TILE_BYTES];
    float sc[kS];
    float red[8][128];
    float csum[8][32];
    float hst[8][4][2];
    uint32_t x_pk[4][kD / 2];
    uint32_t opart[8][OP_PITCH];
    uint32_t q_pk[kDH / 2];
    float wmax[NCW];
    float wsum[NCW];
    float stat[4][2];
    float hfin[16];
    uint32_t act_pk[4][8];
    unsigned long long full[NSTAGE];
    unsigned long long gate;
    unsigned long long hdone;
    unsigned long long fdone;
    unsigned long long fbar;
    unsigned long long xbar;
    uint32_t cnt[NSTAGE];
};
static_assert(sizeof(Smem) + 1024 <= 232448, "smem too large");

struct __align__(128) Scratch {
    unsigned int epoch;
    unsigned int pad0[31];
    unsigned int gate;
    unsigned int pad1[31];
    unsigned long long hbuf[HREP][4 * kD / 2];
    unsigned long long qx[NCTA][4][kDH];
    unsigned long long part1[NCTA][kH][16];
    unsigned long long part2[NCTA][NFFN][16];
};
__device__ Scratch g_scratch;
#define TSTAMP(i)
#define TSTAMPW(i, w)
#define PSTAMP(i)

__device__ __forceinline__ uint32_t smem_u32(const void* p) { return (uint32_t)__cvta_generic_to_shared(p); }
__device__ __forceinline__ void mbar_init(uint32_t bar, uint32_t cnt) {
    asm volatile("mbarrier.init.shared::cta.b64 [%0], %1;" ::"r"(bar), "r"(cnt) : "memory");
}
__device__ __forceinline__ void mbar_expect_tx(uint32_t bar, uint32_t bytes) {
    asm volatile("mbarrier.arrive.expect_tx.shared::cta.b64 _, [%0], %1;" ::"r"(bar), "r"(bytes) : "memory");
}
__device__ __forceinline__ void mbar_arrive(uint32_t bar) {
    asm volatile("mbarrier.arrive.shared::cta.b64 _, [%0];" ::"r"(bar) : "memory");
}
__device__ __forceinline__ bool mbar_try(uint32_t bar, uint32_t parity) {
    uint32_t ok;
    asm volatile(
        "{\n.reg .pred p;\n"
        "mbarrier.try_wait.parity.shared::cta.b64 p, [%1], %2;\n"
        "selp.u32 %0, 1, 0, p;\n}"
        : "=r"(ok) : "r"(bar), "r"(parity) : "memory");
    return ok != 0;
}
__device__ __forceinline__ void mbar_wait(uint32_t bar, uint32_t parity) {
    if (mbar_try(bar, parity)) return;
    const uint32_t t0 = clock();
#pragma unroll 1
    while (!mbar_try(bar, parity)) {
        if ((uint32_t)clock() - t0 > (1u << 28)) break;
    }
}
__device__ __forceinline__ void bulk_load(uint32_t dst, const void* src, uint32_t bytes, uint32_t bar, uint64_t pol) {
    asm volatile(
        "cp.async.bulk.shared::cluster.global.mbarrier::complete_tx::bytes.L2::cache_hint [%0], [%1], %2, [%3], %4;"
        ::"r"(dst), "l"(src), "r"(bytes), "r"(bar), "l"(pol) : "memory");
}

__device__ __forceinline__ float bf16r(float v) {
    uint32_t r;
    asm("cvt.rn.bf16x2.f32 %0, %1, %2;" : "=r"(r) : "f"(v), "f"(0.f));
    return __uint_as_float(r);
}
__device__ __forceinline__ uint32_t pack_bf16(float lo, float hi) {
    uint32_t r;
    asm("cvt.rn.bf16x2.f32 %0, %1, %2;" : "=r"(r) : "f"(hi), "f"(lo));
    return r;
}
__device__ __forceinline__ float bf_lo(uint32_t w) { return __uint_as_float(w << 16); }
__device__ __forceinline__ float bf_hi(uint32_t w) { return __uint_as_float(w & 0xffff0000u); }

__device__ __forceinline__ void mma16816(float (&d)[4], uint32_t a0, uint32_t a1, uint32_t a2, uint32_t a3,
                                         uint32_t b0, uint32_t b1) {
    asm volatile(
        "mma.sync.aligned.m16n8k16.row.col.f32.bf16.bf16.f32 {%0,%1,%2,%3}, {%4,%5,%6,%7}, {%8,%9}, {%0,%1,%2,%3};"
        : "+f"(d[0]), "+f"(d[1]), "+f"(d[2]), "+f"(d[3])
        : "r"(a0), "r"(a1), "r"(a2), "r"(a3), "r"(b0), "r"(b1));
}
__device__ __forceinline__ float fast_sqrt(float v) {
    float r;
    asm("sqrt.approx.f32 %0, %1;" : "=f"(r) : "f"(v));
    return r;
}
__device__ __forceinline__ uint4 ldg128(const void* p) {
    uint4 v;
    asm volatile("ld.global.nc.L1::no_allocate.v4.u32 {%0,%1,%2,%3}, [%4];" : "=r"(v.x), "=r"(v.y), "=r"(v.z), "=r"(v.w) : "l"(p));
    return v;
}
__device__ __forceinline__ uint4 lds128(uint32_t a) {
    uint4 v;
    asm volatile("ld.shared.v4.u32 {%0,%1,%2,%3}, [%4];" : "=r"(v.x), "=r"(v.y), "=r"(v.z), "=r"(v.w) : "r"(a));
    return v;
}
__device__ __forceinline__ uint32_t prmt_lo(uint32_t a, uint32_t b) { return __byte_perm(a, b, 0x5410); }
__device__ __forceinline__ uint32_t prmt_hi(uint32_t a, uint32_t b) { return __byte_perm(a, b, 0x7632); }

__device__ __forceinline__ unsigned long long ll_pack(uint32_t d, uint32_t tag) {
    return ((unsigned long long)tag << 32) | d;
}
__device__ __forceinline__ void ll_store1(unsigned long long* p, uint32_t d, uint32_t tag) {
    asm volatile("st.relaxed.gpu.global.b64 [%0], %1;" ::"l"(p), "l"(ll_pack(d, tag)) : "memory");
}
__device__ __forceinline__ void ll_store2(unsigned long long* p, uint32_t d0, uint32_t d1, uint32_t tag) {
    asm volatile("st.relaxed.gpu.global.v2.b64 [%0], {%1, %2};" ::"l"(p), "l"(ll_pack(d0, tag)), "l"(ll_pack(d1, tag))
                 : "memory");
}
template <int N>
__device__ __forceinline__ void ll_wait_batch(const unsigned long long* p, int stride, uint32_t tag, uint32_t have,
                                              uint32_t (&d0)[N], uint32_t (&d1)[N]) {
    unsigned long long a[N], c[N];
#pragma unroll
    for (int i = 0; i < N; i++) { a[i] = (unsigned long long)have << 32; c[i] = a[i]; }
    uint32_t spins = 0;
#pragma unroll 1
    while (true) {
#pragma unroll
        for (int i = 0; i < N; i++)
            asm volatile(
                "{\n.reg .pred p, q;\n.reg .b32 lo, hi;\n"
                "mov.b64 {lo, hi}, %0;\nsetp.ne.u32 p, hi, %3;\n"
                "mov.b64 {lo, hi}, %1;\nsetp.ne.or.u32 p, hi, %3, p;\n"
                "@p ld.relaxed.gpu.global.v2.b64 {%0, %1}, [%2];\n}"
                : "+l"(a[i]), "+l"(c[i]) : "l"(p + stride * i), "r"(tag) : "memory");
        uint32_t bad = 0;
#pragma unroll
        for (int i = 0; i < N; i++) bad |= ((uint32_t)(a[i] >> 32) ^ tag) | ((uint32_t)(c[i] >> 32) ^ tag);
        if (__all_sync(0xffffffffu, bad == 0) || ++spins > SPIN_LIMIT) break;
    }
#pragma unroll
    for (int i = 0; i < N; i++) { d0[i] = (uint32_t)a[i]; d1[i] = (uint32_t)c[i]; }
}
__device__ __forceinline__ void ldsm4t(uint32_t (&r)[4], uint32_t a) {
    asm volatile("ldmatrix.sync.aligned.m8n8.x4.trans.shared.b16 {%0,%1,%2,%3}, [%4];"
                 : "=r"(r[0]), "=r"(r[1]), "=r"(r[2]), "=r"(r[3]) : "r"(a));
}
__device__ __forceinline__ void ll_wait1(const unsigned long long* p, uint32_t tag, uint32_t& d) {
    uint32_t spins = 0;
#pragma unroll 1
    while (true) {
        unsigned long long a;
        asm volatile("ld.relaxed.gpu.global.b64 %0, [%1];" : "=l"(a) : "l"(p) : "memory");
        d = (uint32_t)a;
        if ((uint32_t)(a >> 32) == tag || ++spins > SPIN_LIMIT) break;
    }
}
__device__ __forceinline__ uint32_t ln_pair(uint32_t v, uint32_t m2, float rinv) {
    uint32_t d;
    asm("sub.rn.bf16x2 %0, %1, %2;" : "=r"(d) : "r"(v), "r"(m2));
    return pack_bf16(bf_lo(d) * rinv, bf_hi(d) * rinv);
}
__device__ __forceinline__ float warp_sum(float v) {
#pragma unroll
    for (int o = 16; o > 0; o >>= 1) v += __shfl_xor_sync(0xffffffffu, v, o);
    return v;
}
__device__ __forceinline__ float warp_max(float v) {
#pragma unroll
    for (int o = 16; o > 0; o >>= 1) v = fmaxf(v, __shfl_xor_sync(0xffffffffu, v, o));
    return v;
}

__device__ __forceinline__ void bar_sync(int id, int n) { asm volatile("bar.sync %0, %1;" ::"r"(id), "r"(n) : "memory"); }

__global__ void __launch_bounds__(NCT, 1)
fused_decode_kernel(const __nv_bfloat16* __restrict__ x, const __nv_bfloat16* __restrict__ kc,
                    const __nv_bfloat16* __restrict__ vc, const __nv_bfloat16* __restrict__ wq,
                    const __nv_bfloat16* __restrict__ w2, __nv_bfloat16* __restrict__ out, Scratch* __restrict__ gs,
                    const __grid_constant__ CUtensorMap tmo, const __grid_constant__ CUtensorMap tm1,
                    const __grid_constant__ CUtensorMap tm3) {
    extern __shared__ uint8_t smem_raw[];
    Smem& sm = *reinterpret_cast<Smem*>(smem_raw + ((1024u - (smem_u32(smem_raw) & 1023u)) & 1023u));
    const int tid = threadIdx.x, warp = tid >> 5, lane = tid & 31;
    const int bh = blockIdx.x, b = bh >> 5, h = bh & 31;
    const int g = lane >> 2, t = lane & 3;
    const uint8_t* ksrc = reinterpret_cast<const uint8_t*>(kc) + (size_t)bh * (kS * kDH * 2);
    const uint8_t* vsrc = reinterpret_cast<const uint8_t*>(vc) + (size_t)bh * (kS * kDH * 2);
    TSTAMP(0);
    uint64_t pol;
    asm volatile("createpolicy.fractional.L2::evict_first.b64 %0, 1.0;" : "=l"(pol));

    const int ch = warp & 1, ks = warp >> 1;
    uint4 raw[4];
    {
        const __nv_bfloat16* p = wq + (size_t)(128 * b + 16 * ks + 4 * t) * (kH * kDH) + h * kDH + 64 * ch + 8 * g;
#pragma unroll
        for (int r = 0; r < 4; r++) raw[r] = ldg128(p + (size_t)r * (kH * kDH));
    }
    uint32_t ep;
    asm volatile("ld.relaxed.gpu.global.u32 %0, [%1];" : "=r"(ep) : "l"(&gs->epoch) : "memory");

    if (warp == NCW - 1) {
        if (lane == 0) {
            mbar_init(smem_u32(&sm.xbar), 1);
#pragma unroll
            for (int s = 0; s < NSTAGE; s++) {
                mbar_init(smem_u32(&sm.full[s]), 1);
                sm.cnt[s] = 0;
            }
            mbar_init(smem_u32(&sm.gate), 1);
            mbar_init(smem_u32(&sm.hdone), 1);
            mbar_init(smem_u32(&sm.fdone), 1);
            mbar_init(smem_u32(&sm.fbar), 1);
            asm volatile("fence.mbarrier_init.release.cluster;" ::: "memory");
            asm volatile("fence.proxy.async.shared::cta;" ::: "memory");
            PSTAMP(0);
            mbar_expect_tx(smem_u32(&sm.xbar), 4 * kD * 2);
            asm volatile("cp.async.bulk.shared::cluster.global.mbarrier::complete_tx::bytes [%0], [%1], %2, [%3];"
                         ::"r"(smem_u32(sm.x_pk)), "l"(x), "r"(4 * kD * 2), "r"(smem_u32(&sm.xbar)) : "memory");
#pragma unroll 1
            for (int s = 0; s < NWO; s++) {
                mbar_expect_tx(smem_u32(&sm.full[s]), TILE_BYTES);
                asm volatile("cp.async.bulk.tensor.3d.shared::cluster.global.mbarrier::complete_tx::bytes [%0], [%1, {%3, %4, %5}], [%2];"
                             ::"r"(smem_u32(sm.ring[s])), "l"(reinterpret_cast<uint64_t>(&tmo)), "r"(smem_u32(&sm.full[s])),
                               "r"(0), "r"(h * kDH + 32 * s), "r"(0) : "memory");
            }
#pragma unroll 1
            for (int s = NWO; s < NSTAGE; s++) {
                mbar_expect_tx(smem_u32(&sm.full[s]), TILE_BYTES);
                bulk_load(smem_u32(sm.ring[s]), ksrc + (size_t)(s - NWO) * TILE_BYTES, TILE_BYTES, smem_u32(&sm.full[s]), pol);
            }
            PSTAMP(1);
        }
        __syncwarp();
        mbar_wait(smem_u32(&sm.xbar), 0);
        const int row = lane >> 3, l8 = lane & 7;
        float s = 0.f;
        uint4 xv[8];
#pragma unroll
        for (int i = 0; i < 8; i++) {
            xv[i] = lds128(smem_u32(sm.x_pk[row]) + (8 * i + l8) * 16);
            s += ((bf_lo(xv[i].x) + bf_hi(xv[i].x)) + (bf_lo(xv[i].y) + bf_hi(xv[i].y))) +
                 ((bf_lo(xv[i].z) + bf_hi(xv[i].z)) + (bf_lo(xv[i].w) + bf_hi(xv[i].w)));
        }
#pragma unroll
        for (int o = 1; o < 8; o <<= 1) s += __shfl_xor_sync(0xffffffffu, s, o);
        const float mean = s * (1.f / kD);
        float q0 = 0.f, q1 = 0.f;
#pragma unroll
        for (int i = 0; i < 8; i++) {
            const uint32_t w[4] = {xv[i].x, xv[i].y, xv[i].z, xv[i].w};
#pragma unroll
            for (int k = 0; k < 4; k++) {
                const float e0 = bf_lo(w[k]) - mean, e1 = bf_hi(w[k]) - mean;
                q0 = fmaf(e0, e0, q0); q1 = fmaf(e1, e1, q1);
            }
        }
        float s2 = q0 + q1;
#pragma unroll
        for (int o = 1; o < 8; o <<= 1) s2 += __shfl_xor_sync(0xffffffffu, s2, o);
        const float sd = bf16r(fast_sqrt(bf16r(bf16r(s2 * (1.f / kD)) + 1e-5f)));
        if (l8 == 0) {
            sm.stat[row][0] = __uint_as_float(pack_bf16(mean, mean));
            sm.stat[row][1] = __fdividef(1.f, sd);
        }
    }
    PSTAMP(2);
    __syncthreads();
    const uint32_t tag = ep + 1u;
    {
        const float2 st = *reinterpret_cast<const float2*>(&sm.stat[g & 3][0]);
        const uint2 xw = *reinterpret_cast<const uint2*>(&sm.x_pk[g & 3][64 * b + 8 * ks + 2 * t]);
        const uint32_t b0 = ln_pair(xw.x, __float_as_uint(st.x), st.y);
        const uint32_t b1 = ln_pair(xw.y, __float_as_uint(st.x), st.y);
        float d[4][4];
        const uint32_t* r0 = reinterpret_cast<const uint32_t*>(&raw[0]);
        const uint32_t* r1 = reinterpret_cast<const uint32_t*>(&raw[1]);
        const uint32_t* r2 = reinterpret_cast<const uint32_t*>(&raw[2]);
        const uint32_t* r3 = reinterpret_cast<const uint32_t*>(&raw[3]);
#pragma unroll
        for (int i = 0; i < 4; i++) {
            d[i][0] = d[i][1] = d[i][2] = d[i][3] = 0.f;
            mma16816(d[i], prmt_lo(r0[i], r1[i]), prmt_hi(r0[i], r1[i]), prmt_lo(r2[i], r3[i]), prmt_hi(r2[i], r3[i]), b0, b1);
        }
        float* qp = sm.sc + (ks * 4 + 2 * (t & 1)) * kDH + 64 * ch + 8 * g + 4 * (t >> 1);
        const bool hi = t >= 2;
        *reinterpret_cast<float4*>(qp) = hi ? make_float4(d[2][0], d[2][2], d[3][0], d[3][2])
                                            : make_float4(d[0][0], d[0][2], d[1][0], d[1][2]);
        *reinterpret_cast<float4*>(qp + kDH) = hi ? make_float4(d[2][1], d[2][3], d[3][1], d[3][3])
                                                  : make_float4(d[0][1], d[0][3], d[1][1], d[1][3]);
    }
    PSTAMP(3);
    __syncthreads();
    {
        float a = 0.f;
#pragma unroll
        for (int k = 0; k < 8; k++) a += sm.sc[k * 512 + tid];
        ll_store1(&gs->qx[(tid >> 7) * 32 + h][b][tid & 127], __float_as_uint(a), tag);
    }
    TSTAMP(15);
    PSTAMP(4);

    auto release_slot = [&](int slot, int i) {
        __syncwarp();
        if (lane == 0) {
            uint32_t old;
            asm volatile("atom.relaxed.cta.shared::cta.inc.u32 %0, [%1], %2;"
                         : "=r"(old) : "r"(smem_u32(&sm.cnt[slot])), "n"(NCW - 1) : "memory");
            if (old == NCW - 1) {
                const int nx = i + NSTAGE - NWO;
                const uint32_t bar = smem_u32(&sm.full[slot]);
                mbar_expect_tx(bar, TILE_BYTES);
                const uint8_t* src = (nx < NTILE) ? ksrc + (size_t)nx * TILE_BYTES : vsrc + (size_t)(nx - NTILE) * TILE_BYTES;
                bulk_load(smem_u32(sm.ring[slot]), src, TILE_BYTES, bar, pol);
                if (nx == 2 * NTILE - 1) asm volatile("red.relaxed.gpu.global.add.u32 [%0], 1;" ::"l"(&gs->gate) : "memory");
            }
        }
    };
    auto gather_q = [&]() {
        uint32_t d;
        ll_wait1(&gs->qx[bh][tid >> 7][tid & 127], tag, d);
        sm.red[tid >> 7][tid & 127] = __uint_as_float(d);
    };

    const uint32_t ldsm_row = (lane & 7) + ((lane >> 4) << 3);
    const uint32_t ldsm_col = ((lane >> 3) & 1) * 8;
    uint32_t wf[8][2][4];
    if (QFIRST) gather_q();
    PSTAMP(5);
#pragma unroll
    for (int T = 0; T < NWO; T++) {
        mbar_wait(smem_u32(&sm.full[T]), 0);
        const uint32_t base = smem_u32(sm.ring[T]) + (warp >> 1) * 4096 + ldsm_row * 128;
        const uint32_t c0 = 4 * (warp & 1) + (ldsm_col >> 3), sw = lane & 7;
        ldsm4t(wf[2 * T][0], base + ((c0 ^ sw) << 4));
        ldsm4t(wf[2 * T][1], base + (((c0 + 2) ^ sw) << 4));
        ldsm4t(wf[2 * T + 1][0], base + 16 * 128 + ((c0 ^ sw) << 4));
        ldsm4t(wf[2 * T + 1][1], base + 16 * 128 + (((c0 + 2) ^ sw) << 4));
        release_slot(T, T);
    }
    TSTAMP(12);
    PSTAMP(6);
    if (!QFIRST) gather_q();
    PSTAMP(7);
    __syncthreads();
    if (tid < kDH) {
        float qv = (sm.red[0][tid] + sm.red[1][tid]) + (sm.red[2][tid] + sm.red[3][tid]);
        reinterpret_cast<__nv_bfloat16*>(sm.q_pk)[tid] = __float2bfloat16_rn(qv);
    }
    __syncthreads();
    TSTAMP(1);
    PSTAMP(8);

    int slot = NWO % NSTAGE; uint32_t ph = (NWO / NSTAGE) & 1;
    const bool is_ffn = bh < NFFN;

    float lmax = -INFINITY;
    {
        uint4 qf[4];
#pragma unroll
        for (int i = 0; i < 4; i++) qf[i] = lds128(smem_u32(sm.q_pk) + (t + 4 * (i ^ (g & 1))) * 16);
        const uint32_t lane_off = (8 * warp + g) * 256 + t * 16;
#pragma unroll 1
        for (int j = 0; j < NTILE; j++) {
            mbar_wait(smem_u32(&sm.full[slot]), ph);
            const uint32_t base = smem_u32(sm.ring[slot]) + lane_off;
            float d0[4] = {0.f, 0.f, 0.f, 0.f}, d1[4] = {0.f, 0.f, 0.f, 0.f};
            uint4 va[4];
#pragma unroll
            for (int i = 0; i < 4; i++) va[i] = lds128(base + 64 * (i ^ (g & 1)));
#pragma unroll
            for (int i = 0; i < 4; i++) {
                mma16816(d0, va[i].x, va[i].x, va[i].y, va[i].y, qf[i].x, qf[i].y);
                mma16816(d1, va[i].z, va[i].z, va[i].w, va[i].w, qf[i].z, qf[i].w);
            }
            release_slot(slot, NWO + j);
            float sv = (g & 1) ? d0[1] + d1[1] : d0[0] + d1[0];
            sv = bf16r(bf16r(sv) * 0.08838834764831845f);
            lmax = fmaxf(lmax, sv);
            if (t == 0) sm.sc[j * TILE_KEYS + 8 * warp + g] = sv;
            if (++slot == NSTAGE) { slot = 0; ph ^= 1; }
        }
    }
    TSTAMP(2);

    {
        lmax = warp_max(lmax);
        if (lane == 0) sm.wmax[warp] = lmax;
        __syncthreads();
        float gmax = sm.wmax[0];
#pragma unroll
        for (int i = 1; i < NCW; i++) gmax = fmaxf(gmax, sm.wmax[i]);
        float4 a = *reinterpret_cast<float4*>(&sm.sc[tid * 4]);
        float4 c = *reinterpret_cast<float4*>(&sm.sc[2048 + tid * 4]);
        a.x = __expf(a.x - gmax); a.y = __expf(a.y - gmax); a.z = __expf(a.z - gmax); a.w = __expf(a.w - gmax);
        c.x = __expf(c.x - gmax); c.y = __expf(c.y - gmax); c.z = __expf(c.z - gmax); c.w = __expf(c.w - gmax);
        float ls = ((a.x + a.y) + (a.z + a.w)) + ((c.x + c.y) + (c.z + c.w));
        ls = warp_sum(ls);
        if (lane == 0) sm.wsum[warp] = ls;
        __syncthreads();
        float tot = 0.f;
#pragma unroll
        for (int i = 0; i < NCW; i++) tot += sm.wsum[i];
        const float inv = __fdividef(1.f, tot);
        a.x = bf16r(a.x * inv); a.y = bf16r(a.y * inv); a.z = bf16r(a.z * inv); a.w = bf16r(a.w * inv);
        c.x = bf16r(c.x * inv); c.y = bf16r(c.y * inv); c.z = bf16r(c.z * inv); c.w = bf16r(c.w * inv);
        *reinterpret_cast<float4*>(&sm.sc[tid * 4]) = a;
        *reinterpret_cast<float4*>(&sm.sc[2048 + tid * 4]) = c;
        __syncthreads();
    }
    TSTAMP(3);

    const uint32_t gate_target = tag * NCTA;
    uint32_t gate_val = gate_target - 1u;
    bool gate_done = false;
    auto open_gate = [&]() {
        asm volatile("prefetch.global.L2 [%0];" ::"l"(&gs->part1[bh][lane][0]));
        asm volatile("prefetch.global.L2 [%0];" ::"l"(&gs->hbuf[bh & (HREP - 1)][16 * lane]));
        asm volatile("prefetch.global.L2 [%0];" ::"l"(&gs->hbuf[bh & (HREP - 1)][512 + 16 * lane]));
#pragma unroll
        for (int i = 0; i < 4; i++)
            if (32 * i + lane < NFFN) asm volatile("prefetch.global.L2 [%0];" ::"l"(&gs->part2[bh][32 * i + lane][0]));
        if (lane == 0) mbar_arrive(smem_u32(&sm.gate));
    };
    {
        float acc[8];
#pragma unroll
        for (int i = 0; i < 8; i++) acc[i] = 0.f;
        const int dh = warp & 1, kg = warp >> 1, ks4 = lane >> 3, c8 = lane & 7;
        const uint32_t lane_off = (16 * kg + 4 * ks4) * 256 + 128 * dh + 16 * c8;
#pragma unroll 1
        for (int jv = 0; jv < NTILE; jv++) {
            const float4 pw = *reinterpret_cast<const float4*>(&sm.sc[jv * TILE_KEYS + 16 * kg + 4 * ks4]);
            mbar_wait(smem_u32(&sm.full[slot]), ph);
            const uint32_t base = smem_u32(sm.ring[slot]) + lane_off;
            uint4 v[4];
#pragma unroll
            for (int i = 0; i < 4; i++) v[i] = lds128(base + i * 256);
            const float pv[4] = {pw.x, pw.y, pw.z, pw.w};
#pragma unroll
            for (int i = 0; i < 4; i++) {
                acc[0] = fmaf(pv[i], bf_lo(v[i].x), acc[0]);
                acc[1] = fmaf(pv[i], bf_hi(v[i].x), acc[1]);
                acc[2] = fmaf(pv[i], bf_lo(v[i].y), acc[2]);
                acc[3] = fmaf(pv[i], bf_hi(v[i].y), acc[3]);
                acc[4] = fmaf(pv[i], bf_lo(v[i].z), acc[4]);
                acc[5] = fmaf(pv[i], bf_hi(v[i].z), acc[5]);
                acc[6] = fmaf(pv[i], bf_lo(v[i].w), acc[6]);
                acc[7] = fmaf(pv[i], bf_hi(v[i].w), acc[7]);
            }
            if (jv < NTILE - NSTAGE) release_slot(slot, NWO + NTILE + jv);
            if (warp == 6 && !gate_done) {
                if ((int32_t)(gate_val - gate_target) >= 0) { open_gate(); gate_done = true; }
                else asm volatile("ld.relaxed.gpu.global.u32 %0, [%1];" : "=r"(gate_val) : "l"(&gs->gate) : "memory");
            }
            if (jv == JP) {
                if (t < 2) ll_store2(&gs->part1[b * 32 + 2 * warp + t][h][2 * g], 0u, 0u, tag - 1u);
                if (warp == 0 && !(lane & 1))
                    ll_store2(&gs->hbuf[lane >> 3][b * 256 + 32 * (h >> 2) + 8 * ((lane >> 1) & 3) + 2 * (h & 3)], 0u, 0u, tag - 1u);
                if (is_ffn && warp >= 8) {
#pragma unroll
                    for (int i = 0; i < 2; i++) {
                        unsigned long long* dst = &gs->part2[2 * (t & 1) * 32 + 4 * (warp - 8) + 2 * i + (t >> 1)][bh][2 * g];
                        ll_store2(dst, 0u, 0u, tag - 1u);
                        ll_store2(dst + 32 * NFFN * 16, 0u, 0u, tag - 1u);
                    }
                }
            }
            if (++slot == NSTAGE) { slot = 0; ph ^= 1; }
        }
        TSTAMP(4);
        const bool up = lane & 16, mid = lane & 8;
        float r[4];
#pragma unroll
        for (int i = 0; i < 4; i++) {
            const float send = up ? acc[i] : acc[i + 4];
            const float keep = up ? acc[i + 4] : acc[i];
            r[i] = keep + __shfl_xor_sync(0xffffffffu, send, 16);
        }
        const float s0 = (mid ? r[2] : r[0]) + __shfl_xor_sync(0xffffffffu, mid ? r[0] : r[2], 8);
        const float s1 = (mid ? r[3] : r[1]) + __shfl_xor_sync(0xffffffffu, mid ? r[1] : r[3], 8);
        const int ksd = 4 * dh + (c8 >> 1);
        sm.opart[kg][16 * (ksd >> 1) + 4 * ks4 + 2 * (ksd & 1) + (c8 & 1)] = pack_bf16(s0, s1);
        __syncthreads();
    }
    TSTAMP(11);

    {
        float d[4][4];
#pragma unroll
        for (int i = 0; i < 4; i++) { d[i][0] = d[i][1] = d[i][2] = d[i][3] = 0.f; }
#pragma unroll
        for (int i = 0; i < 4; i++) {
            const uint4 bw = lds128(smem_u32(&sm.opart[g][16 * i + 4 * t]));
            mma16816(d[0], wf[2 * i][0][0], wf[2 * i][0][1], wf[2 * i][0][2], wf[2 * i][0][3], bw.x, bw.y);
            mma16816(d[1], wf[2 * i][1][0], wf[2 * i][1][1], wf[2 * i][1][2], wf[2 * i][1][3], bw.x, bw.y);
            mma16816(d[2], wf[2 * i + 1][0][0], wf[2 * i + 1][0][1], wf[2 * i + 1][0][2], wf[2 * i + 1][0][3], bw.z, bw.w);
            mma16816(d[3], wf[2 * i + 1][1][0], wf[2 * i + 1][1][1], wf[2 * i + 1][1][2], wf[2 * i + 1][1][3], bw.z, bw.w);
        }
        const float a0 = (d[0][0] + d[2][0]) + (d[0][1] + d[2][1]), b0 = (d[0][2] + d[2][2]) + (d[0][3] + d[2][3]);
        const float a1 = (d[1][0] + d[3][0]) + (d[1][1] + d[3][1]), b1 = (d[1][2] + d[3][2]) + (d[1][3] + d[3][3]);
        const bool odd = t & 1;
        float ya = (odd ? a1 : a0) + __shfl_xor_sync(0xffffffffu, odd ? a0 : a1, 1);
        float yb = (odd ? b1 : b0) + __shfl_xor_sync(0xffffffffu, odd ? b0 : b1, 1);
        ya += __shfl_xor_sync(0xffffffffu, ya, 2);
        yb += __shfl_xor_sync(0xffffffffu, yb, 2);
        if (t < 2) ll_store2(&gs->part1[b * 32 + 2 * warp + t][h][2 * g], __float_as_uint(ya), __float_as_uint(yb), tag);
    }
    TSTAMP(5);

    const uint32_t w1s = smem_u32(sm.ring[0]), w3s = w1s + kD * 32, w2s = smem_u32(sm.ring[1]);
    if (warp < 2) {
        if (warp == 0) {
            const int pp = lane & 7;
            const unsigned long long* src = &gs->part1[bh][8 * (lane >> 3)][2 * pp];
            const __nv_bfloat16* xr = reinterpret_cast<const __nv_bfloat16*>(sm.x_pk[b]) + 16 * h;
            const float xA = __bfloat162float(xr[pp]), xB = __bfloat162float(xr[pp + 8]);
            unsigned long long* dst = &gs->hbuf[lane >> 3][b * 256 + 32 * (h >> 2) + 8 * (pp >> 1) + 2 * (h & 3)];
            mbar_wait(smem_u32(&sm.gate), 0);
            TSTAMP(6);
            uint32_t d0[8], d1[8];
            ll_wait_batch<8>(src, 16, tag, tag - 1u, d0, d1);
            float v0 = 0.f, v1 = 0.f, v2 = 0.f, v3 = 0.f;
#pragma unroll
            for (int i = 0; i < 8; i += 2) {
                v0 += __uint_as_float(d0[i]); v1 += __uint_as_float(d1[i]);
                v2 += __uint_as_float(d0[i + 1]); v3 += __uint_as_float(d1[i + 1]);
            }
            v0 += v2; v1 += v3;
            v0 += __shfl_xor_sync(0xffffffffu, v0, 8);  v1 += __shfl_xor_sync(0xffffffffu, v1, 8);
            v0 += __shfl_xor_sync(0xffffffffu, v0, 16); v1 += __shfl_xor_sync(0xffffffffu, v1, 16);
            const float hA = bf16r(xA + bf16r(v0));
            const float hB = bf16r(xB + bf16r(v1));
            const float nA = __shfl_xor_sync(0xffffffffu, hA, 1), nB = __shfl_xor_sync(0xffffffffu, hB, 1);
            if (!(lane & 1)) ll_store2(dst, pack_bf16(hA, nA), pack_bf16(hB, nB), tag);
            if (lane < 8) *reinterpret_cast<float2*>(&sm.hfin[2 * lane]) = make_float2(hA, hB);
            __syncwarp();
            if (lane == 0) mbar_arrive(smem_u32(&sm.hdone));
            TSTAMP(7);
        }
        {
            const int pq = 4 * warp + (lane & 3);
            const unsigned long long* src = &gs->part2[bh][lane >> 2][2 * pq];
            __nv_bfloat16* op = out + b * kD + 16 * h + pq + ((lane & 4) ? 8 : 0);
            mbar_wait(smem_u32(&sm.fdone), 0);
            const float2 hf = *reinterpret_cast<const float2*>(&sm.hfin[2 * pq]);
            uint32_t d0[14], d1[14];
            ll_wait_batch<14>(src, 128, tag, tag - 1u, d0, d1);
            TSTAMP(14);
            float v0 = 0.f, v1 = 0.f, v2 = 0.f, v3 = 0.f;
#pragma unroll
            for (int i = 0; i < 14; i += 2) {
                v0 += __uint_as_float(d0[i]); v1 += __uint_as_float(d1[i]);
                v2 += __uint_as_float(d0[i + 1]); v3 += __uint_as_float(d1[i + 1]);
            }
            v0 += v2; v1 += v3;
#pragma unroll
            for (int o = 4; o <= 16; o <<= 1) {
                v0 += __shfl_xor_sync(0xffffffffu, v0, o);
                v1 += __shfl_xor_sync(0xffffffffu, v1, o);
            }
            const float res = (lane & 4) ? hf.y + bf16r(v1) : hf.x + bf16r(v0);
            if (lane < 8) *op = __float2bfloat16_rn(res);
            if (bh == 0 && tid == 0) *reinterpret_cast<volatile unsigned int*>(&gs->epoch) = tag;
        }
        TSTAMP(10);
    } else if (warp == 7) {
        if (is_ffn) {
            const int f0 = bh * 16;
            const uint32_t bar = smem_u32(&sm.fbar);
            if (lane == 0) mbar_expect_tx(bar, 2 * kD * 32 + 16 * kD * 2);
            __syncwarp();
            if (lane < 4) {
                const uint32_t dst = ((lane & 1) ? w3s : w1s) + (lane >> 1) * (256 * 32);
                const uint64_t tm = reinterpret_cast<uint64_t>((lane & 1) ? &tm3 : &tm1);
                asm volatile("cp.async.bulk.tensor.2d.shared::cluster.global.mbarrier::complete_tx::bytes [%0], [%1, {%3, %4}], [%2];"
                             ::"r"(dst), "l"(tm), "r"(bar), "r"(f0), "r"((lane >> 1) * 256) : "memory");
            } else if (lane == 4) {
                asm volatile("cp.async.bulk.shared::cluster.global.mbarrier::complete_tx::bytes [%0], [%1], %2, [%3];"
                             ::"r"(w2s), "l"(w2 + (size_t)f0 * kD), "r"(16 * kD * 2), "r"(bar) : "memory");
            }
        }
    } else if (warp == 6) {
        if (!gate_done) {
            uint32_t spins = 0;
#pragma unroll 1
            while (true) {
                asm volatile("ld.relaxed.gpu.global.u32 %0, [%1];" : "=r"(gate_val) : "l"(&gs->gate) : "memory");
                if ((int32_t)(gate_val - gate_target) >= 0 || ++spins > SPIN_LIMIT) break;
                __nanosleep(100);
            }
            open_gate();
        }
    } else if (warp >= 8 && is_ffn) {
        const int fw = warp - 8, u = tid - 256;
        const unsigned long long* src = &gs->hbuf[bh & (HREP - 1)][(g & 3) * 256 + 32 * fw + 8 * t];
        unsigned long long* dst = &gs->part2[2 * (t & 1) * 32 + 4 * fw + (t >> 1)][bh][2 * g];
        mbar_wait(smem_u32(&sm.fbar), 0);
        uint32_t a1[4][4], a3[4][4], a2[4][4];
#pragma unroll
        for (int i = 0; i < 4; i++) {
            const uint32_t off = (64 * fw + 16 * i + ldsm_row) * 32 + ldsm_col * 2;
            ldsm4t(a1[i], w1s + off);
            ldsm4t(a3[i], w3s + off);
            ldsm4t(a2[i], w2s + ldsm_row * (kD * 2) + (64 * fw + 16 * i + ldsm_col) * 2);
        }
        uint32_t bw[8];
        mbar_wait(smem_u32(&sm.hdone), 0);
        {
            uint32_t e0[4], e1[4];
            ll_wait_batch<4>(src, 2, tag, (g < 4) ? tag - 1u : tag, e0, e1);
            const uint32_t fill = (g == 4) ? 0x3f803f80u : 0u;
#pragma unroll
            for (int i = 0; i < 4; i++) { bw[2 * i] = (g < 4) ? e0[i] : fill; bw[2 * i + 1] = (g < 4) ? e1[i] : fill; }
        }
        TSTAMPW(8, 8);
        float dg[2][4], du[2][4];
#pragma unroll
        for (int i = 0; i < 2; i++) { dg[i][0] = dg[i][1] = dg[i][2] = dg[i][3] = 0.f; du[i][0] = du[i][1] = du[i][2] = du[i][3] = 0.f; }
#pragma unroll
        for (int i = 0; i < 4; i++) {
            mma16816(dg[i & 1], a1[i][0], a1[i][1], a1[i][2], a1[i][3], bw[2 * i], bw[2 * i + 1]);
            mma16816(du[i & 1], a3[i][0], a3[i][1], a3[i][2], a3[i][3], bw[2 * i], bw[2 * i + 1]);
        }
        {
            float p1[4], p2[4];
#pragma unroll
            for (int i = 0; i < 4; i++) {
                const float l0 = bf_lo(bw[2 * i]), h0 = bf_hi(bw[2 * i]), l1 = bf_lo(bw[2 * i + 1]), h1 = bf_hi(bw[2 * i + 1]);
                p1[i] = (l0 + h0) + (l1 + h1);
                p2[i] = fmaf(l0, l0, h0 * h0) + fmaf(l1, l1, h1 * h1);
            }
            float s1 = (p1[0] + p1[1]) + (p1[2] + p1[3]), s2 = (p2[0] + p2[1]) + (p2[2] + p2[3]);
            s1 += __shfl_xor_sync(0xffffffffu, s1, 1); s2 += __shfl_xor_sync(0xffffffffu, s2, 1);
            s1 += __shfl_xor_sync(0xffffffffu, s1, 2); s2 += __shfl_xor_sync(0xffffffffu, s2, 2);
            if (t == 0 && g < 4) *reinterpret_cast<float2*>(&sm.hst[fw][g][0]) = make_float2(s1, s2);
        }
        if (t < 2) {
            float* dq = &sm.red[fw][(g * 2 + t) * 8];
            *reinterpret_cast<float4*>(dq) = make_float4(dg[0][0] + dg[1][0], dg[0][1] + dg[1][1], dg[0][2] + dg[1][2], dg[0][3] + dg[1][3]);
            *reinterpret_cast<float4*>(dq + 4) = make_float4(du[0][0] + du[1][0], du[0][1] + du[1][1], du[0][2] + du[1][2], du[0][3] + du[1][3]);
        } else if (t == 2) {
            *reinterpret_cast<float4*>(&sm.csum[fw][4 * g]) =
                make_float4(dg[0][0] + dg[1][0], dg[0][2] + dg[1][2], du[0][0] + du[1][0], du[0][2] + du[1][2]);
        }
        bar_sync(1, 256);
        TSTAMPW(13, 8);
        if (u < 128) {
            const int bt = 2 * ((u >> 3) & 1) + (u & 1);
            const int ci = 4 * (u >> 4) + ((u >> 1) & 3);
            float S[2] = {0.f, 0.f}, C[2] = {0.f, 0.f}, s1[2] = {0.f, 0.f}, s2[2] = {0.f, 0.f};
#pragma unroll
            for (int w = 0; w < 8; w++) {
                S[w & 1] += sm.red[w][u];
                C[w & 1] += sm.csum[w][ci];
                const float2 st = *reinterpret_cast<const float2*>(&sm.hst[w][bt][0]);
                s1[w & 1] += st.x; s2[w & 1] += st.y;
            }
            const float mean = (s1[0] + s1[1]) * (1.f / kD);
            const float var = fmaxf(fmaf(-mean, mean, (s2[0] + s2[1]) * (1.f / kD)), 0.f);
            const float sd = bf16r(fast_sqrt(bf16r(bf16r(var) + 1e-5f)));
            const float val = bf16r(__fdividef(fmaf(-bf16r(mean), C[0] + C[1], S[0] + S[1]), sd));
            const float other = __shfl_xor_sync(0xffffffffu, val, 4);
            const float sl = bf16r(__fdividef(val, 1.f + __expf(-val)));
            const float act = sl * other;
            const int f = (u >> 4) + 8 * ((u >> 1) & 1);
            const int wpos = 2 * ((f >> 1) & 3) + (f >> 3);
            if (!(u & 4)) reinterpret_cast<__nv_bfloat16*>(sm.act_pk[bt])[2 * wpos + (f & 1)] = __float2bfloat16_rn(act);
        }
        bar_sync(1, 256);
        {
            const uint2 ab = *reinterpret_cast<const uint2*>(&sm.act_pk[g & 3][2 * t]);
            float e[4][4];
#pragma unroll
            for (int i = 0; i < 4; i++) {
                e[i][0] = e[i][1] = e[i][2] = e[i][3] = 0.f;
                mma16816(e[i], a2[i][0], a2[i][1], a2[i][2], a2[i][3], ab.x, ab.y);
            }
            const bool mt = t >= 2;
#pragma unroll
            for (int i = 0; i < 2; i++) {
                const float r0 = mt ? e[2 * i + 1][0] : e[2 * i][0], r1 = mt ? e[2 * i + 1][1] : e[2 * i][1];
                const float r2 = mt ? e[2 * i + 1][2] : e[2 * i][2], r3 = mt ? e[2 * i + 1][3] : e[2 * i][3];
                ll_store2(dst + 2 * i * NFFN * 16, __float_as_uint(r0), __float_as_uint(r2), tag);
                ll_store2(dst + (2 * i + 32) * NFFN * 16, __float_as_uint(r1), __float_as_uint(r3), tag);
            }
        }
        if (u == 0) mbar_arrive(smem_u32(&sm.fdone));
        TSTAMPW(9, 8);
    } else if (warp == 8) {
        mbar_wait(smem_u32(&sm.hdone), 0);
        uint32_t d0[1], d1[1];
        ll_wait_batch<1>(&gs->hbuf[bh & (HREP - 1)][32 * lane], 0, tag, tag - 1u, d0, d1);
        if (lane == 0) mbar_arrive(smem_u32(&sm.fdone));
    }
}

}

extern "C" void kernel_launch(void* const* d_in, const int* in_sizes, int n_in, void* d_out, int out_size) {
    (void)in_sizes; (void)n_in; (void)out_size;
    const __nv_bfloat16* x  = (const __nv_bfloat16*)d_in[0];
    const __nv_bfloat16* kc = (const __nv_bfloat16*)d_in[1];
    const __nv_bfloat16* vc = (const __nv_bfloat16*)d_in[2];
    const __nv_bfloat16* wq = (const __nv_bfloat16*)d_in[3];
    const __nv_bfloat16* wo = (const __nv_bfloat16*)d_in[4];
    const __nv_bfloat16* w1 = (const __nv_bfloat16*)d_in[6];
    const __nv_bfloat16* w3 = (const __nv_bfloat16*)d_in[7];
    const __nv_bfloat16* w2 = (const __nv_bfloat16*)d_in[8];
    typedef CUresult (*EncodeFn)(CUtensorMap*, CUtensorMapDataType, cuuint32_t, void*, const cuuint64_t*, const cuuint64_t*,
                                 const cuuint32_t*, const cuuint32_t*, CUtensorMapInterleave, CUtensorMapSwizzle,
                                 CUtensorMapL2promotion, CUtensorMapFloatOOBfill);
    void* fn = nullptr;
    cudaDriverEntryPointQueryResult qres;
    cudaGetDriverEntryPoint("cuTensorMapEncodeTiled", &fn, cudaEnableDefault, &qres);
    EncodeFn encode = (EncodeFn)fn;
    CUtensorMap tmo, tm1, tm3;
    {
        const cuuint64_t gdim[3] = {64, (cuuint64_t)(kH * kDH), 8};
        const cuuint64_t gstr[2] = {(cuuint64_t)kD * 2, 128};
        const cuuint32_t box[3] = {64, 32, 8};
        const cuuint32_t estr[3] = {1, 1, 1};
        encode(&tmo, CU_TENSOR_MAP_DATA_TYPE_BFLOAT16, 3, (void*)wo, gdim, gstr, box, estr, CU_TENSOR_MAP_INTERLEAVE_NONE,
               CU_TENSOR_MAP_SWIZZLE_128B, CU_TENSOR_MAP_L2_PROMOTION_NONE, CU_TENSOR_MAP_FLOAT_OOB_FILL_NONE);
    }
    {
        const cuuint64_t gdim[2] = {(cuuint64_t)kF, (cuuint64_t)kD};
        const cuuint64_t gstr[1] = {(cuuint64_t)kF * 2};
        const cuuint32_t box[2] = {16, 256};
        const cuuint32_t estr[2] = {1, 1};
        encode(&tm1, CU_TENSOR_MAP_DATA_TYPE_BFLOAT16, 2, (void*)w1, gdim, gstr, box, estr, CU_TENSOR_MAP_INTERLEAVE_NONE,
               CU_TENSOR_MAP_SWIZZLE_NONE, FFN_PROMO, CU_TENSOR_MAP_FLOAT_OOB_FILL_NONE);
        encode(&tm3, CU_TENSOR_MAP_DATA_TYPE_BFLOAT16, 2, (void*)w3, gdim, gstr, box, estr, CU_TENSOR_MAP_INTERLEAVE_NONE,
               CU_TENSOR_MAP_SWIZZLE_NONE, FFN_PROMO, CU_TENSOR_MAP_FLOAT_OOB_FILL_NONE);
    }
    const int smem_bytes = (int)sizeof(Smem) + 1024;
    cudaFuncSetAttribute(fused_decode_kernel, cudaFuncAttributeMaxDynamicSharedMemorySize, smem_bytes);
    void* gs = nullptr;
    cudaGetSymbolAddress(&gs, g_scratch);
    fused_decode_kernel<<<NCTA, NCT, smem_bytes, cudaStreamPerThread>>>(x, kc, vc, wq, w2, (__nv_bfloat16*)d_out,
                                                                       (Scratch*)gs, tmo, tm1, tm3);
}
```

```cpp
#include <cuda_runtime.h>
#include <cuda.h>
#include <cuda_bf16.h>
#include <stdint.h>

namespace {

constexpr int kH = 32, kS = 4096, kDH = 128, kD = 512, kF = 1792;
constexpr int NCTA = 128;
constexpr int NFFN = 112;
constexpr int NCW = 16;
constexpr int NCT = NCW * 32;
#define NSTAGE_ 4
#define FFN_PROMO CU_TENSOR_MAP_L2_PROMOTION_L2_64B
#define QFIRST 0
constexpr int TILE_KEYS = 128;
constexpr int TILE_BYTES = TILE_KEYS * kDH * 2;
constexpr int NSTAGE = NSTAGE_;
constexpr int NTILE = kS / TILE_KEYS;
constexpr int NWO = 4;
#define VSPIN 100
#define JF 31
#define JP_ 20
constexpr int JP = JP_;
#define HREP_ 4
constexpr int HREP = HREP_;
constexpr int OP_PITCH = 80;
constexpr uint32_t SPIN_LIMIT = 1u << 20;
static_assert(NSTAGE == NWO, "ring layout");

struct __align__(1024) Smem {
    uint8_t ring[NSTAGE][TILE_BYTES];
    uint8_t ffn[3][kD * 32];
    float sc[kS];
    float red[8][128];
    float csum[8][32];
    float hst[8][4][2];
    uint32_t x_pk[4][kD / 2];
    uint32_t opart[8][OP_PITCH];
    uint32_t q_pk[kDH / 2];
    float wmax[NCW];
    float wsum[NCW];
    float stat[4][2];
    unsigned long long own1[8];
    unsigned long long own2[8];
    uint32_t hown[8];
    uint32_t act_pk[4][8];
    unsigned long long full[NSTAGE];
    unsigned long long hdone;
    unsigned long long o1bar;
    unsigned long long fdone;
    unsigned long long fbar;
    unsigned long long xbar;
    unsigned long long k0bar;
    uint32_t cnt[NSTAGE];
};
static_assert(sizeof(Smem) + 1024 <= 232448, "smem too large");

struct __align__(128) Scratch {
    unsigned int epoch;
    unsigned int pad0[31];
    unsigned long long hbuf[HREP][NCTA][16];
    unsigned long long qx[NCTA][4][kDH];
    unsigned long long part1[NCTA][kH][8];
    unsigned long long part2[NCTA][NFFN][8];
};
__device__ Scratch g_scratch;
#define TSTAMP(i)
#define TSTAMPW(i, w)
#define PSTAMP(i)
#define WSTAMP(i)

__device__ __forceinline__ uint32_t smem_u32(const void* p) { return (uint32_t)__cvta_generic_to_shared(p); }
__device__ __forceinline__ void mbar_init(uint32_t bar, uint32_t cnt) {
    asm volatile("mbarrier.init.shared::cta.b64 [%0], %1;" ::"r"(bar), "r"(cnt) : "memory");
}
__device__ __forceinline__ void mbar_expect_tx(uint32_t bar, uint32_t bytes) {
    asm volatile("mbarrier.arrive.expect_tx.shared::cta.b64 _, [%0], %1;" ::"r"(bar), "r"(bytes) : "memory");
}
__device__ __forceinline__ void mbar_arrive(uint32_t bar) {
    asm volatile("mbarrier.arrive.shared::cta.b64 _, [%0];" ::"r"(bar) : "memory");
}
__device__ __forceinline__ bool mbar_try(uint32_t bar, uint32_t parity) {
    uint32_t ok;
    asm volatile(
        "{\n.reg .pred p;\n"
        "mbarrier.try_wait.parity.shared::cta.b64 p, [%1], %2;\n"
        "selp.u32 %0, 1, 0, p;\n}"
        : "=r"(ok) : "r"(bar), "r"(parity) : "memory");
    return ok != 0;
}
__device__ __forceinline__ void mbar_wait(uint32_t bar, uint32_t parity) {
    if (mbar_try(bar, parity)) return;
    const uint32_t t0 = clock();
#pragma unroll 1
    while (!mbar_try(bar, parity)) {
        if ((uint32_t)clock() - t0 > (1u << 28)) break;
    }
}
__device__ __forceinline__ void mbar_spin(uint32_t bar, uint32_t parity) {
    const uint32_t t0 = clock();
#pragma unroll 1
    while (true) {
        uint32_t ok;
        asm volatile(
            "{\n.reg .pred p;\n"
            "mbarrier.test_wait.parity.shared::cta.b64 p, [%1], %2;\n"
            "selp.u32 %0, 1, 0, p;\n}"
            : "=r"(ok) : "r"(bar), "r"(parity) : "memory");
        if (ok || (uint32_t)clock() - t0 > (1u << 28)) break;
    }
}
__device__ __forceinline__ void bulk_load(uint32_t dst, const void* src, uint32_t bytes, uint32_t bar, uint64_t pol) {
    asm volatile(
        "cp.async.bulk.shared::cluster.global.mbarrier::complete_tx::bytes.L2::cache_hint [%0], [%1], %2, [%3], %4;"
        ::"r"(dst), "l"(src), "r"(bytes), "r"(bar), "l"(pol) : "memory");
}

__device__ __forceinline__ float bf16r(float v) {
    uint32_t r;
    asm("cvt.rn.bf16x2.f32 %0, %1, %2;" : "=r"(r) : "f"(v), "f"(0.f));
    return __uint_as_float(r);
}
__device__ __forceinline__ uint32_t pack_bf16(float lo, float hi) {
    uint32_t r;
    asm("cvt.rn.bf16x2.f32 %0, %1, %2;" : "=r"(r) : "f"(hi), "f"(lo));
    return r;
}
__device__ __forceinline__ float bf_lo(uint32_t w) { return __uint_as_float(w << 16); }
__device__ __forceinline__ float bf_hi(uint32_t w) { return __uint_as_float(w & 0xffff0000u); }

__device__ __forceinline__ void mma16816(float (&d)[4], uint32_t a0, uint32_t a1, uint32_t a2, uint32_t a3,
                                         uint32_t b0, uint32_t b1) {
    asm volatile(
        "mma.sync.aligned.m16n8k16.row.col.f32.bf16.bf16.f32 {%0,%1,%2,%3}, {%4,%5,%6,%7}, {%8,%9}, {%0,%1,%2,%3};"
        : "+f"(d[0]), "+f"(d[1]), "+f"(d[2]), "+f"(d[3])
        : "r"(a0), "r"(a1), "r"(a2), "r"(a3), "r"(b0), "r"(b1));
}
__device__ __forceinline__ float fast_sqrt(float v) {
    float r;
    asm("sqrt.approx.f32 %0, %1;" : "=f"(r) : "f"(v));
    return r;
}
__device__ __forceinline__ uint4 ldg128(const void* p) {
    uint4 v;
    asm volatile("ld.global.nc.L1::no_allocate.v4.u32 {%0,%1,%2,%3}, [%4];" : "=r"(v.x), "=r"(v.y), "=r"(v.z), "=r"(v.w) : "l"(p));
    return v;
}
__device__ __forceinline__ uint4 lds128(uint32_t a) {
    uint4 v;
    asm volatile("ld.shared.v4.u32 {%0,%1,%2,%3}, [%4];" : "=r"(v.x), "=r"(v.y), "=r"(v.z), "=r"(v.w) : "r"(a));
    return v;
}
__device__ __forceinline__ uint32_t prmt_lo(uint32_t a, uint32_t b) { return __byte_perm(a, b, 0x5410); }
__device__ __forceinline__ uint32_t prmt_hi(uint32_t a, uint32_t b) { return __byte_perm(a, b, 0x7632); }

__device__ __forceinline__ unsigned long long ll_pack(uint32_t d, uint32_t tag) {
    return ((unsigned long long)tag << 32) | d;
}
__device__ __forceinline__ void ll_store1(unsigned long long* p, uint32_t d, uint32_t tag) {
    asm volatile("st.relaxed.gpu.global.b64 [%0], %1;" ::"l"(p), "l"(ll_pack(d, tag)) : "memory");
}
__device__ __forceinline__ void ll_store2(unsigned long long* p, uint32_t d0, uint32_t d1, uint32_t tag) {
    asm volatile("st.relaxed.gpu.global.v2.b64 [%0], {%1, %2};" ::"l"(p), "l"(ll_pack(d0, tag)), "l"(ll_pack(d1, tag))
                 : "memory");
}
template <int N>
__device__ __forceinline__ void ll_wait_batch(const unsigned long long* p, int stride, uint32_t tag, uint32_t have,
                                              int own, uint32_t o0, uint32_t o1, uint32_t (&d0)[N], uint32_t (&d1)[N]) {
    unsigned long long a[N], c[N];
#pragma unroll
    for (int i = 0; i < N; i++) {
        a[i] = (i == own) ? ll_pack(o0, tag) : (unsigned long long)have << 32;
        c[i] = (i == own) ? ll_pack(o1, tag) : (unsigned long long)have << 32;
    }
    uint32_t spins = 0;
#pragma unroll 1
    while (true) {
#pragma unroll
        for (int i = 0; i < N; i++)
            asm volatile(
                "{\n.reg .pred p, q;\n.reg .b32 lo, hi;\n"
                "mov.b64 {lo, hi}, %0;\nsetp.ne.u32 p, hi, %3;\n"
                "mov.b64 {lo, hi}, %1;\nsetp.ne.or.u32 p, hi, %3, p;\n"
                "@p ld.relaxed.gpu.global.v2.b64 {%0, %1}, [%2];\n}"
                : "+l"(a[i]), "+l"(c[i]) : "l"(p + stride * i), "r"(tag) : "memory");
        uint32_t bad = 0;
#pragma unroll
        for (int i = 0; i < N; i++) bad |= ((uint32_t)(a[i] >> 32) ^ tag) | ((uint32_t)(c[i] >> 32) ^ tag);
        if (__all_sync(0xffffffffu, bad == 0) || ++spins > SPIN_LIMIT) break;
    }
#pragma unroll
    for (int i = 0; i < N; i++) { d0[i] = (uint32_t)a[i]; d1[i] = (uint32_t)c[i]; }
}
__device__ __forceinline__ unsigned long long pk_make(float a, float b, uint32_t tag) {
    const uint32_t lo = ((__float_as_uint(a) + 8u) & ~15u) | (tag & 15u);
    const uint32_t hi = ((__float_as_uint(b) + 8u) & ~15u) | ((tag >> 4) & 15u);
    return ((unsigned long long)hi << 32) | lo;
}
__device__ __forceinline__ void pk_store(unsigned long long* p, unsigned long long w) {
    asm volatile("st.relaxed.gpu.global.b64 [%0], %1;" ::"l"(p), "l"(w) : "memory");
}
template <int N>
__device__ __forceinline__ void pk_wait_batch(const unsigned long long* p, int stride, uint32_t tag, int own,
                                              unsigned long long o0, unsigned long long o1, float (&sum)[4]) {
    const unsigned long long want = pk_make(0.f, 0.f, tag) & 0x0000000f0000000full;
    unsigned long long a[N], c[N];
#pragma unroll
    for (int i = 0; i < N; i++) {
        a[i] = (i == own) ? o0 : ~want;
        c[i] = (i == own) ? o1 : ~want;
    }
    uint32_t spins = 0;
#pragma unroll 1
    while (true) {
#pragma unroll
        for (int i = 0; i < N; i++) {
            const unsigned long long x = ((a[i] ^ want) | (c[i] ^ want)) & 0x0000000f0000000full;
            asm volatile("{\n.reg .pred p;\nsetp.ne.u64 p, %3, 0;\n@p ld.relaxed.gpu.global.v2.b64 {%0, %1}, [%2];\n}"
                         : "+l"(a[i]), "+l"(c[i]) : "l"(p + stride * i), "l"(x) : "memory");
        }
        unsigned long long bad = 0;
#pragma unroll
        for (int i = 0; i < N; i++) bad |= (a[i] ^ want) | (c[i] ^ want);
        if (__all_sync(0xffffffffu, (bad & 0x0000000f0000000full) == 0) || ++spins > SPIN_LIMIT) break;
    }
    float s[2][4];
#pragma unroll
    for (int k = 0; k < 4; k++) { s[0][k] = 0.f; s[1][k] = 0.f; }
#pragma unroll
    for (int i = 0; i < N; i++) {
        s[i & 1][0] += __uint_as_float((uint32_t)a[i] & ~15u);
        s[i & 1][1] += __uint_as_float((uint32_t)(a[i] >> 32) & ~15u);
        s[i & 1][2] += __uint_as_float((uint32_t)c[i] & ~15u);
        s[i & 1][3] += __uint_as_float((uint32_t)(c[i] >> 32) & ~15u);
    }
#pragma unroll
    for (int k = 0; k < 4; k++) sum[k] = s[0][k] + s[1][k];
}
__device__ __forceinline__ void ldsm4t(uint32_t (&r)[4], uint32_t a) {
    asm volatile("ldmatrix.sync.aligned.m8n8.x4.trans.shared.b16 {%0,%1,%2,%3}, [%4];"
                 : "=r"(r[0]), "=r"(r[1]), "=r"(r[2]), "=r"(r[3]) : "r"(a));
}
__device__ __forceinline__ void ll_wait1(const unsigned long long* p, uint32_t tag, uint32_t& d) {
    uint32_t spins = 0;
#pragma unroll 1
    while (true) {
        unsigned long long a;
        asm volatile("ld.relaxed.gpu.global.b64 %0, [%1];" : "=l"(a) : "l"(p) : "memory");
        d = (uint32_t)a;
        if ((uint32_t)(a >> 32) == tag || ++spins > SPIN_LIMIT) break;
    }
}
__device__ __forceinline__ uint32_t ln_pair(uint32_t v, uint32_t m2, float rinv) {
    uint32_t d;
    asm("sub.rn.bf16x2 %0, %1, %2;" : "=r"(d) : "r"(v), "r"(m2));
    return pack_bf16(bf_lo(d) * rinv, bf_hi(d) * rinv);
}
__device__ __forceinline__ float warp_sum(float v) {
#pragma unroll
    for (int o = 16; o > 0; o >>= 1) v += __shfl_xor_sync(0xffffffffu, v, o);
    return v;
}
__device__ __forceinline__ float warp_max(float v) {
#pragma unroll
    for (int o = 16; o > 0; o >>= 1) v = fmaxf(v, __shfl_xor_sync(0xffffffffu, v, o));
    return v;
}

__device__ __forceinline__ void bar_sync(int id, int n) { asm volatile("bar.sync %0, %1;" ::"r"(id), "r"(n) : "memory"); }

__global__ void __launch_bounds__(NCT, 1)
fused_decode_kernel(const __nv_bfloat16* __restrict__ x, const __nv_bfloat16* __restrict__ kc,
                    const __nv_bfloat16* __restrict__ vc, const __nv_bfloat16* __restrict__ wq,
                    __nv_bfloat16* __restrict__ out, Scratch* __restrict__ gs,
                    const __grid_constant__ CUtensorMap tmo, const __grid_constant__ CUtensorMap tm1,
                    const __grid_constant__ CUtensorMap tm3, const __grid_constant__ CUtensorMap tm2) {
    extern __shared__ uint8_t smem_raw[];
    Smem& sm = *reinterpret_cast<Smem*>(smem_raw + ((1024u - (smem_u32(smem_raw) & 1023u)) & 1023u));
    const int tid = threadIdx.x, warp = tid >> 5, lane = tid & 31;
    const int bh = blockIdx.x, b = bh >> 5, h = bh & 31;
    const int g = lane >> 2, t = lane & 3;
    const uint8_t* ksrc = reinterpret_cast<const uint8_t*>(kc) + (size_t)bh * (kS * kDH * 2);
    const uint8_t* vsrc = reinterpret_cast<const uint8_t*>(vc) + (size_t)bh * (kS * kDH * 2);
    TSTAMP(0);
    uint64_t pol;
    asm volatile("createpolicy.fractional.L2::evict_first.b64 %0, 1.0;" : "=l"(pol));

    const int ch = warp & 1, ks = warp >> 1;
    uint4 raw[4];
    {
        const __nv_bfloat16* p = wq + (size_t)(128 * b + 16 * ks + 4 * t) * (kH * kDH) + h * kDH + 64 * ch + 8 * g;
#pragma unroll
        for (int r = 0; r < 4; r++) raw[r] = ldg128(p + (size_t)r * (kH * kDH));
    }
    uint32_t ep;
    asm volatile("ld.relaxed.gpu.global.u32 %0, [%1];" : "=r"(ep) : "l"(&gs->epoch) : "memory");

    if (warp == NCW - 1) {
        if (lane == 0) {
            mbar_init(smem_u32(&sm.xbar), 1);
            mbar_init(smem_u32(&sm.k0bar), 1);
#pragma unroll
            for (int s = 0; s < NSTAGE; s++) {
                mbar_init(smem_u32(&sm.full[s]), 1);
                sm.cnt[s] = 0;
            }
            mbar_init(smem_u32(&sm.hdone), 1);
            mbar_init(smem_u32(&sm.o1bar), 1);
            mbar_init(smem_u32(&sm.fdone), bh < NFFN ? 8 : 1);
            mbar_init(smem_u32(&sm.fbar), 1);
            asm volatile("fence.mbarrier_init.release.cluster;" ::: "memory");
            asm volatile("fence.proxy.async.shared::cta;" ::: "memory");
            PSTAMP(0);
            mbar_expect_tx(smem_u32(&sm.fbar), 2 * kD * 32 + 16 * kD * 2);
            mbar_expect_tx(smem_u32(&sm.xbar), 4 * kD * 2);
            asm volatile("cp.async.bulk.shared::cluster.global.mbarrier::complete_tx::bytes [%0], [%1], %2, [%3];"
                         ::"r"(smem_u32(sm.x_pk)), "l"(x), "r"(4 * kD * 2), "r"(smem_u32(&sm.xbar)) : "memory");
#pragma unroll 1
            for (int s = 0; s < NWO; s++) {
                mbar_expect_tx(smem_u32(&sm.full[s]), TILE_BYTES);
                asm volatile("cp.async.bulk.tensor.3d.shared::cluster.global.mbarrier::complete_tx::bytes [%0], [%1, {%3, %4, %5}], [%2];"
                             ::"r"(smem_u32(sm.ring[s])), "l"(reinterpret_cast<uint64_t>(&tmo)), "r"(smem_u32(&sm.full[s])),
                               "r"(0), "r"(h * kDH + 32 * s), "r"(0) : "memory");
            }
            mbar_expect_tx(smem_u32(&sm.k0bar), TILE_BYTES);
            bulk_load(smem_u32(sm.ffn), ksrc, TILE_BYTES, smem_u32(&sm.k0bar), pol);
            PSTAMP(1);
        }
        __syncwarp();
        mbar_wait(smem_u32(&sm.xbar), 0);
        const int row = lane >> 3, l8 = lane & 7;
        float s = 0.f;
        uint4 xv[8];
#pragma unroll
        for (int i = 0; i < 8; i++) {
            xv[i] = lds128(smem_u32(sm.x_pk[row]) + (8 * i + l8) * 16);
            s += ((bf_lo(xv[i].x) + bf_hi(xv[i].x)) + (bf_lo(xv[i].y) + bf_hi(xv[i].y))) +
                 ((bf_lo(xv[i].z) + bf_hi(xv[i].z)) + (bf_lo(xv[i].w) + bf_hi(xv[i].w)));
        }
#pragma unroll
        for (int o = 1; o < 8; o <<= 1) s += __shfl_xor_sync(0xffffffffu, s, o);
        const float mean = s * (1.f / kD);
        float q0 = 0.f, q1 = 0.f;
#pragma unroll
        for (int i = 0; i < 8; i++) {
            const uint32_t w[4] = {xv[i].x, xv[i].y, xv[i].z, xv[i].w};
#pragma unroll
            for (int k = 0; k < 4; k++) {
                const float e0 = bf_lo(w[k]) - mean, e1 = bf_hi(w[k]) - mean;
                q0 = fmaf(e0, e0, q0); q1 = fmaf(e1, e1, q1);
            }
        }
        float s2 = q0 + q1;
#pragma unroll
        for (int o = 1; o < 8; o <<= 1) s2 += __shfl_xor_sync(0xffffffffu, s2, o);
        const float sd = bf16r(fast_sqrt(bf16r(bf16r(s2 * (1.f / kD)) + 1e-5f)));
        if (l8 == 0) {
            sm.stat[row][0] = __uint_as_float(pack_bf16(mean, mean));
            sm.stat[row][1] = __fdividef(1.f, sd);
        }
    }
    PSTAMP(2);
    __syncthreads();
    const uint32_t tag = ep + 1u;
    {
        const float2 st = *reinterpret_cast<const float2*>(&sm.stat[g & 3][0]);
        const uint2 xw = *reinterpret_cast<const uint2*>(&sm.x_pk[g & 3][64 * b + 8 * ks + 2 * t]);
        const uint32_t b0 = ln_pair(xw.x, __float_as_uint(st.x), st.y);
        const uint32_t b1 = ln_pair(xw.y, __float_as_uint(st.x), st.y);
        float d[4][4];
        const uint32_t* r0 = reinterpret_cast<const uint32_t*>(&raw[0]);
        const uint32_t* r1 = reinterpret_cast<const uint32_t*>(&raw[1]);
        const uint32_t* r2 = reinterpret_cast<const uint32_t*>(&raw[2]);
        const uint32_t* r3 = reinterpret_cast<const uint32_t*>(&raw[3]);
#pragma unroll
        for (int i = 0; i < 4; i++) {
            d[i][0] = d[i][1] = d[i][2] = d[i][3] = 0.f;
            mma16816(d[i], prmt_lo(r0[i], r1[i]), prmt_hi(r0[i], r1[i]), prmt_lo(r2[i], r3[i]), prmt_hi(r2[i], r3[i]), b0, b1);
        }
        float* qp = sm.sc + (ks * 4 + 2 * (t & 1)) * kDH + 64 * ch + 8 * g + 4 * (t >> 1);
        const bool hi = t >= 2;
        *reinterpret_cast<float4*>(qp) = hi ? make_float4(d[2][0], d[2][2], d[3][0], d[3][2])
                                            : make_float4(d[0][0], d[0][2], d[1][0], d[1][2]);
        *reinterpret_cast<float4*>(qp + kDH) = hi ? make_float4(d[2][1], d[2][3], d[3][1], d[3][3])
                                                  : make_float4(d[0][1], d[0][3], d[1][1], d[1][3]);
    }
    PSTAMP(3);
    __syncthreads();
    {
        float a = 0.f;
#pragma unroll
        for (int k = 0; k < 8; k++) a += sm.sc[k * 512 + tid];
        if ((tid >> 7) != b) ll_store1(&gs->qx[(tid >> 7) * 32 + h][b][tid & 127], __float_as_uint(a), tag);
        else sm.red[b][tid & 127] = a;
    }
    TSTAMP(15);
    PSTAMP(4);

    auto release_slot = [&](int slot, int nx) {
        __syncwarp();
        if (lane == 0) {
            uint32_t old;
            asm volatile("atom.relaxed.cta.shared::cta.inc.u32 %0, [%1], %2;"
                         : "=r"(old) : "r"(smem_u32(&sm.cnt[slot])), "n"(NCW - 1) : "memory");
            if (old == NCW - 1) {
                const uint32_t bar = smem_u32(&sm.full[slot]);
                mbar_expect_tx(bar, TILE_BYTES);
                const uint8_t* src = (nx < NTILE) ? ksrc + (size_t)nx * TILE_BYTES : vsrc + (size_t)(nx - NTILE) * TILE_BYTES;
                bulk_load(smem_u32(sm.ring[slot]), src, TILE_BYTES, bar, pol);
            }
        }
    };
    auto gather_q = [&]() {
        if ((tid >> 7) != b) {
            uint32_t d;
            ll_wait1(&gs->qx[bh][tid >> 7][tid & 127], tag, d);
            sm.red[tid >> 7][tid & 127] = __uint_as_float(d);
        }
    };

    const uint32_t ldsm_row = (lane & 7) + ((lane >> 4) << 3);
    const uint32_t ldsm_col = ((lane >> 3) & 1) * 8;
    uint32_t wf[8][2][4];
    if (QFIRST) gather_q();
    PSTAMP(5);
#pragma unroll
    for (int T = 0; T < NWO; T++) {
        mbar_wait(smem_u32(&sm.full[T]), 0);
        const uint32_t base = smem_u32(sm.ring[T]) + (warp >> 1) * 4096 + ldsm_row * 128;
        const uint32_t c0 = 4 * (warp & 1) + (ldsm_col >> 3), sw = lane & 7;
        ldsm4t(wf[2 * T][0], base + ((c0 ^ sw) << 4));
        ldsm4t(wf[2 * T][1], base + (((c0 + 2) ^ sw) << 4));
        ldsm4t(wf[2 * T + 1][0], base + 16 * 128 + ((c0 ^ sw) << 4));
        ldsm4t(wf[2 * T + 1][1], base + 16 * 128 + (((c0 + 2) ^ sw) << 4));
        release_slot(T, T + 1);
    }
    TSTAMP(12);
    PSTAMP(6);
    if (!QFIRST) gather_q();
    PSTAMP(7);
    __syncthreads();
    if (tid < kDH) {
        float qv = (sm.red[0][tid] + sm.red[1][tid]) + (sm.red[2][tid] + sm.red[3][tid]);
        reinterpret_cast<__nv_bfloat16*>(sm.q_pk)[tid] = __float2bfloat16_rn(qv);
    }
    __syncthreads();
    TSTAMP(1);
    PSTAMP(8);

    int slot = 0; uint32_t ph = 1;
    const bool is_ffn = bh < NFFN;

    float lmax = -INFINITY;
    {
        uint4 qf[4];
#pragma unroll
        for (int i = 0; i < 4; i++) qf[i] = lds128(smem_u32(sm.q_pk) + (t + 4 * (i ^ (g & 1))) * 16);
        const uint32_t lane_off = (8 * warp + g) * 256 + t * 16;
#pragma unroll 1
        for (int j = 0; j < NTILE; j++) {
            mbar_wait(j ? smem_u32(&sm.full[slot]) : smem_u32(&sm.k0bar), j ? ph : 0u);
            const uint32_t base = (j ? smem_u32(sm.ring[slot]) : smem_u32(sm.ffn)) + lane_off;
            float d0[4] = {0.f, 0.f, 0.f, 0.f}, d1[4] = {0.f, 0.f, 0.f, 0.f};
            uint4 va[4];
#pragma unroll
            for (int i = 0; i < 4; i++) va[i] = lds128(base + 64 * (i ^ (g & 1)));
#pragma unroll
            for (int i = 0; i < 4; i++) {
                mma16816(d0, va[i].x, va[i].x, va[i].y, va[i].y, qf[i].x, qf[i].y);
                mma16816(d1, va[i].z, va[i].z, va[i].w, va[i].w, qf[i].z, qf[i].w);
            }
            if (j) release_slot(slot, j + NSTAGE);
            float sv = (g & 1) ? d0[1] + d1[1] : d0[0] + d1[0];
            sv = bf16r(bf16r(sv) * 0.08838834764831845f);
            lmax = fmaxf(lmax, sv);
            if (t == 0) sm.sc[j * TILE_KEYS + 8 * warp + g] = sv;
            if (j && ++slot == NSTAGE) { slot = 0; ph ^= 1; }
        }
    }
    TSTAMP(2);

    {
        lmax = warp_max(lmax);
        if (lane == 0) sm.wmax[warp] = lmax;
        __syncthreads();
        float gmax = sm.wmax[0];
#pragma unroll
        for (int i = 1; i < NCW; i++) gmax = fmaxf(gmax, sm.wmax[i]);
        float4 a = *reinterpret_cast<float4*>(&sm.sc[tid * 4]);
        float4 c = *reinterpret_cast<float4*>(&sm.sc[2048 + tid * 4]);
        a.x = __expf(a.x - gmax); a.y = __expf(a.y - gmax); a.z = __expf(a.z - gmax); a.w = __expf(a.w - gmax);
        c.x = __expf(c.x - gmax); c.y = __expf(c.y - gmax); c.z = __expf(c.z - gmax); c.w = __expf(c.w - gmax);
        float ls = ((a.x + a.y) + (a.z + a.w)) + ((c.x + c.y) + (c.z + c.w));
        ls = warp_sum(ls);
        if (lane == 0) sm.wsum[warp] = ls;
        __syncthreads();
        float tot = 0.f;
#pragma unroll
        for (int i = 0; i < NCW; i++) tot += sm.wsum[i];
        const float inv = __fdividef(1.f, tot);
        a.x = bf16r(a.x * inv); a.y = bf16r(a.y * inv); a.z = bf16r(a.z * inv); a.w = bf16r(a.w * inv);
        c.x = bf16r(c.x * inv); c.y = bf16r(c.y * inv); c.z = bf16r(c.z * inv); c.w = bf16r(c.w * inv);
        *reinterpret_cast<float4*>(&sm.sc[tid * 4]) = a;
        *reinterpret_cast<float4*>(&sm.sc[2048 + tid * 4]) = c;
        __syncthreads();
    }
    TSTAMP(3);

    const uint32_t w1s = smem_u32(sm.ffn[0]), w3s = smem_u32(sm.ffn[1]), w2s = smem_u32(sm.ffn[2]);
    auto stage_ffn = [&]() {
        if (!is_ffn || lane != 0) return;
        const int f0 = bh * 16;
        const uint32_t bar = smem_u32(&sm.fbar);
        if (warp >= 2 && warp < 6) {
            const int c = warp - 2;
            const uint32_t dst = ((c & 1) ? w3s : w1s) + (c >> 1) * (256 * 32);
            const uint64_t tm = reinterpret_cast<uint64_t>((c & 1) ? &tm3 : &tm1);
            asm volatile("cp.async.bulk.tensor.2d.shared::cluster.global.mbarrier::complete_tx::bytes [%0], [%1, {%3, %4}], [%2];"
                         ::"r"(dst), "l"(tm), "r"(bar), "r"(f0), "r"((c >> 1) * 256) : "memory");
        } else if (warp == 7) {
            asm volatile("cp.async.bulk.tensor.3d.shared::cluster.global.mbarrier::complete_tx::bytes [%0], [%1, {%3, %4, %5}], [%2];"
                         ::"r"(w2s), "l"(reinterpret_cast<uint64_t>(&tm2)), "r"(bar), "r"(0), "r"(f0), "r"(0) : "memory");
        }
    };
    {
        float acc[8];
#pragma unroll
        for (int i = 0; i < 8; i++) acc[i] = 0.f;
        const int dh = warp & 1, kg = warp >> 1, ks4 = lane >> 3, c8 = lane & 7;
        const uint32_t lane_off = (16 * kg + 4 * ks4) * 256 + 128 * dh + 16 * c8;
#pragma unroll 1
        for (int jv = 0; jv < NTILE; jv++) {
            const float4 pw = *reinterpret_cast<const float4*>(&sm.sc[jv * TILE_KEYS + 16 * kg + 4 * ks4]);
            if (jv >= VSPIN) mbar_spin(smem_u32(&sm.full[slot]), ph); else mbar_wait(smem_u32(&sm.full[slot]), ph);
            const uint32_t base = smem_u32(sm.ring[slot]) + lane_off;
            uint4 v[4];
#pragma unroll
            for (int i = 0; i < 4; i++) v[i] = lds128(base + i * 256);
            const float pv[4] = {pw.x, pw.y, pw.z, pw.w};
#pragma unroll
            for (int i = 0; i < 4; i++) {
                acc[0] = fmaf(pv[i], bf_lo(v[i].x), acc[0]);
                acc[1] = fmaf(pv[i], bf_hi(v[i].x), acc[1]);
                acc[2] = fmaf(pv[i], bf_lo(v[i].y), acc[2]);
                acc[3] = fmaf(pv[i], bf_hi(v[i].y), acc[3]);
                acc[4] = fmaf(pv[i], bf_lo(v[i].z), acc[4]);
                acc[5] = fmaf(pv[i], bf_hi(v[i].z), acc[5]);
                acc[6] = fmaf(pv[i], bf_lo(v[i].w), acc[6]);
                acc[7] = fmaf(pv[i], bf_hi(v[i].w), acc[7]);
            }
            if (jv < NTILE - NSTAGE) release_slot(slot, NTILE + jv + NSTAGE);
            if (jv == JF) { stage_ffn(); __syncwarp(); }
            if (jv == JP) {
                const unsigned long long stale = pk_make(0.f, 0.f, tag - 1u);
                if (t < 2) pk_store(&gs->part1[b * 32 + 2 * warp + t][h][g], stale);
                if (warp == 0 && lane < 4 * HREP) ll_store2(&gs->hbuf[lane >> 2][bh][2 * (lane & 3)], 0u, 0u, tag - 1u);
                if (is_ffn && warp >= 8) {
#pragma unroll
                    for (int i = 0; i < 2; i++) {
                        unsigned long long* dst = &gs->part2[2 * (t & 1) * 32 + 4 * (warp - 8) + 2 * i + (t >> 1)][bh][g];
                        pk_store(dst, stale);
                        pk_store(dst + 32 * NFFN * 8, stale);
                    }
                }
            }
            if (++slot == NSTAGE) { slot = 0; ph ^= 1; }
        }
        TSTAMP(4);
        const bool up = lane & 16, mid = lane & 8;
        float r[4];
#pragma unroll
        for (int i = 0; i < 4; i++) {
            const float send = up ? acc[i] : acc[i + 4];
            const float keep = up ? acc[i + 4] : acc[i];
            r[i] = keep + __shfl_xor_sync(0xffffffffu, send, 16);
        }
        const float s0 = (mid ? r[2] : r[0]) + __shfl_xor_sync(0xffffffffu, mid ? r[0] : r[2], 8);
        const float s1 = (mid ? r[3] : r[1]) + __shfl_xor_sync(0xffffffffu, mid ? r[1] : r[3], 8);
        const int ksd = 4 * dh + (c8 >> 1);
        sm.opart[kg][16 * (ksd >> 1) + 4 * ks4 + 2 * (ksd & 1) + (c8 & 1)] = pack_bf16(s0, s1);
        __syncthreads();
    }
    TSTAMP(11);

    {
        float d[4][4];
#pragma unroll
        for (int i = 0; i < 4; i++) { d[i][0] = d[i][1] = d[i][2] = d[i][3] = 0.f; }
#pragma unroll
        for (int i = 0; i < 4; i++) {
            const uint4 bw = lds128(smem_u32(&sm.opart[g][16 * i + 4 * t]));
            mma16816(d[0], wf[2 * i][0][0], wf[2 * i][0][1], wf[2 * i][0][2], wf[2 * i][0][3], bw.x, bw.y);
            mma16816(d[1], wf[2 * i][1][0], wf[2 * i][1][1], wf[2 * i][1][2], wf[2 * i][1][3], bw.x, bw.y);
            mma16816(d[2], wf[2 * i + 1][0][0], wf[2 * i + 1][0][1], wf[2 * i + 1][0][2], wf[2 * i + 1][0][3], bw.z, bw.w);
            mma16816(d[3], wf[2 * i + 1][1][0], wf[2 * i + 1][1][1], wf[2 * i + 1][1][2], wf[2 * i + 1][1][3], bw.z, bw.w);
        }
        const float a0 = (d[0][0] + d[2][0]) + (d[0][1] + d[2][1]), b0 = (d[0][2] + d[2][2]) + (d[0][3] + d[2][3]);
        const float a1 = (d[1][0] + d[3][0]) + (d[1][1] + d[3][1]), b1 = (d[1][2] + d[3][2]) + (d[1][3] + d[3][3]);
        const bool odd = t & 1;
        float ya = (odd ? a1 : a0) + __shfl_xor_sync(0xffffffffu, odd ? a0 : a1, 1);
        float yb = (odd ? b1 : b0) + __shfl_xor_sync(0xffffffffu, odd ? b0 : b1, 1);
        ya += __shfl_xor_sync(0xffffffffu, ya, 2);
        yb += __shfl_xor_sync(0xffffffffu, yb, 2);
        const unsigned long long w = pk_make(ya, yb, tag);
        if (warp == (h >> 1)) {
            if (t == (h & 1)) sm.own1[g] = w;
            __syncwarp();
            if (lane == 0) mbar_arrive(smem_u32(&sm.o1bar));
        }
        if (t < 2 && 2 * warp + t != h) pk_store(&gs->part1[b * 32 + 2 * warp + t][h][g], w);
    }
    TSTAMP(5);
    WSTAMP(0);
    if (JF >= NTILE) stage_ffn();

    if (warp < 2) {
        if (warp == 0) {
            const int q4 = lane & 3, sg = lane >> 2;
            const unsigned long long* src = &gs->part1[bh][sg][2 * q4];
            const uint32_t xA = sm.x_pk[b][8 * h + q4], xB = sm.x_pk[b][8 * h + q4 + 4];
            unsigned long long* dst = &gs->hbuf[sg & (HREP - 1)][bh][2 * q4];
            mbar_spin(smem_u32(&sm.o1bar), 0);
            const ulonglong2 mine = *reinterpret_cast<const ulonglong2*>(&sm.own1[2 * q4]);
            TSTAMP(6);
            float v[4];
            pk_wait_batch<4>(src, 64, tag, ((h & 7) == sg) ? (h >> 3) : -1, mine.x, mine.y, v);
            WSTAMP(1);
#pragma unroll
            for (int o = 4; o <= 16; o <<= 1)
#pragma unroll
                for (int k = 0; k < 4; k++) v[k] += __shfl_xor_sync(0xffffffffu, v[k], o);
            const uint32_t wA = pack_bf16(bf_lo(xA) + bf16r(v[0]), bf_hi(xA) + bf16r(v[2]));
            const uint32_t wB = pack_bf16(bf_lo(xB) + bf16r(v[1]), bf_hi(xB) + bf16r(v[3]));
            if (lane < 4 * HREP) ll_store2(dst, wA, wB, tag);
            if (lane < 4) *reinterpret_cast<uint2*>(&sm.hown[2 * q4]) = make_uint2(wA, wB);
            __syncwarp();
            if (lane == 0) mbar_arrive(smem_u32(&sm.hdone));
            TSTAMP(7);
        }
        {
            const int q4 = 2 * warp + (lane & 1), sg = lane >> 1;
            const unsigned long long* src = &gs->part2[bh][sg][2 * q4];
            uint32_t* op = reinterpret_cast<uint32_t*>(out + b * kD + 16 * h + 2 * q4 + ((lane & 2) ? 8 : 0));
            mbar_wait(smem_u32(&sm.fdone), 0);
            const uint32_t hw = sm.hown[2 * q4 + ((lane >> 1) & 1)];
            const ulonglong2 mine = *reinterpret_cast<const ulonglong2*>(&sm.own2[2 * q4]);
            float v[4];
            pk_wait_batch<7>(src, 128, tag, (is_ffn && (bh & 15) == sg) ? (bh >> 4) : -1, mine.x, mine.y, v);
            TSTAMP(14);
#pragma unroll
            for (int o = 2; o <= 16; o <<= 1)
#pragma unroll
                for (int k = 0; k < 4; k++) v[k] += __shfl_xor_sync(0xffffffffu, v[k], o);
            const float f0 = (lane & 2) ? v[1] : v[0], f1 = (lane & 2) ? v[3] : v[2];
            if (lane < 4) *op = pack_bf16(bf_lo(hw) + bf16r(f0), bf_hi(hw) + bf16r(f1));
            if (bh == 0 && tid == 0) *reinterpret_cast<volatile unsigned int*>(&gs->epoch) = tag;
        }
        TSTAMP(10);
    } else if (warp >= 8 && is_ffn) {
        const int fw = warp - 8, u = tid - 256;
        const unsigned long long* src = &gs->hbuf[bh & (HREP - 1)][(g & 3) * 32 + 4 * fw][2 * t];
        unsigned long long* dst = &gs->part2[2 * (t & 1) * 32 + 4 * fw + (t >> 1)][bh][g];
        mbar_wait(smem_u32(&sm.fbar), 0);
        uint32_t a1[4][4], a3[4][4], a2[4][4];
#pragma unroll
        for (int i = 0; i < 4; i++) {
            const uint32_t off = (64 * fw + 16 * i + ldsm_row) * 32 + ((((lane >> 3) ^ (lane >> 2)) & 1) << 4);
            ldsm4t(a1[i], w1s + off);
            ldsm4t(a3[i], w3s + off);
            ldsm4t(a2[i], w2s + fw * 2048 + ldsm_row * 128 + (((2 * i + ((lane >> 3) & 1)) ^ (lane & 7)) << 4));
        }
        uint32_t bw[8];
        mbar_wait(smem_u32(&sm.hdone), 0);
        {
            uint32_t e0[4], e1[4];
            const uint2 mine = *reinterpret_cast<const uint2*>(&sm.hown[2 * t]);
            ll_wait_batch<4>(src, 16, tag, (g < 4) ? tag - 1u : tag, (g == b) ? h - 4 * fw : -1, mine.x, mine.y, e0, e1);
            const uint32_t fill = (g == 4) ? 0x3f803f80u : 0u;
#pragma unroll
            for (int i = 0; i < 4; i++) { bw[2 * i] = (g < 4) ? e0[i] : fill; bw[2 * i + 1] = (g < 4) ? e1[i] : fill; }
        }
        TSTAMPW(8, 8);
        WSTAMP(2);
        float dg[2][4], du[2][4];
#pragma unroll
        for (int i = 0; i < 2; i++) { dg[i][0] = dg[i][1] = dg[i][2] = dg[i][3] = 0.f; du[i][0] = du[i][1] = du[i][2] = du[i][3] = 0.f; }
#pragma unroll
        for (int i = 0; i < 4; i++) {
            mma16816(dg[i & 1], a1[i][0], a1[i][1], a1[i][2], a1[i][3], bw[2 * i], bw[2 * i + 1]);
            mma16816(du[i & 1], a3[i][0], a3[i][1], a3[i][2], a3[i][3], bw[2 * i], bw[2 * i + 1]);
        }
        {
            float p1[4], p2[4];
#pragma unroll
            for (int i = 0; i < 4; i++) {
                const float l0 = bf_lo(bw[2 * i]), h0 = bf_hi(bw[2 * i]), l1 = bf_lo(bw[2 * i + 1]), h1 = bf_hi(bw[2 * i + 1]);
                p1[i] = (l0 + h0) + (l1 + h1);
                p2[i] = fmaf(l0, l0, h0 * h0) + fmaf(l1, l1, h1 * h1);
            }
            float s1 = (p1[0] + p1[1]) + (p1[2] + p1[3]), s2 = (p2[0] + p2[1]) + (p2[2] + p2[3]);
            s1 += __shfl_xor_sync(0xffffffffu, s1, 1); s2 += __shfl_xor_sync(0xffffffffu, s2, 1);
            s1 += __shfl_xor_sync(0xffffffffu, s1, 2); s2 += __shfl_xor_sync(0xffffffffu, s2, 2);
            if (t == 0 && g < 4) *reinterpret_cast<float2*>(&sm.hst[fw][g][0]) = make_float2(s1, s2);
        }
        if (t < 2) {
            float* dq = &sm.red[fw][(g * 2 + t) * 8];
            *reinterpret_cast<float4*>(dq) = make_float4(dg[0][0] + dg[1][0], dg[0][1] + dg[1][1], dg[0][2] + dg[1][2], dg[0][3] + dg[1][3]);
            *reinterpret_cast<float4*>(dq + 4) = make_float4(du[0][0] + du[1][0], du[0][1] + du[1][1], du[0][2] + du[1][2], du[0][3] + du[1][3]);
        } else if (t == 2) {
            *reinterpret_cast<float4*>(&sm.csum[fw][4 * g]) =
                make_float4(dg[0][0] + dg[1][0], dg[0][2] + dg[1][2], du[0][0] + du[1][0], du[0][2] + du[1][2]);
        }
        bar_sync(1, 256);
        TSTAMPW(13, 8);
        if (u < 128) {
            const int bt = 2 * ((u >> 3) & 1) + (u & 1);
            const int ci = 4 * (u >> 4) + ((u >> 1) & 3);
            float S[2] = {0.f, 0.f}, C[2] = {0.f, 0.f}, s1[2] = {0.f, 0.f}, s2[2] = {0.f, 0.f};
#pragma unroll
            for (int w = 0; w < 8; w++) {
                S[w & 1] += sm.red[w][u];
                C[w & 1] += sm.csum[w][ci];
                const float2 st = *reinterpret_cast<const float2*>(&sm.hst[w][bt][0]);
                s1[w & 1] += st.x; s2[w & 1] += st.y;
            }
            const float mean = (s1[0] + s1[1]) * (1.f / kD);
            const float var = fmaxf(fmaf(-mean, mean, (s2[0] + s2[1]) * (1.f / kD)), 0.f);
            const float sd = bf16r(fast_sqrt(bf16r(bf16r(var) + 1e-5f)));
            const float val = bf16r(__fdividef(fmaf(-bf16r(mean), C[0] + C[1], S[0] + S[1]), sd));
            const float other = __shfl_xor_sync(0xffffffffu, val, 4);
            const float sl = bf16r(__fdividef(val, 1.f + __expf(-val)));
            const float act = sl * other;
            const int f = (u >> 4) + 8 * ((u >> 1) & 1);
            const int wpos = 2 * ((f >> 1) & 3) + (f >> 3);
            if (!(u & 4)) reinterpret_cast<__nv_bfloat16*>(sm.act_pk[bt])[2 * wpos + (f & 1)] = __float2bfloat16_rn(act);
        }
        bar_sync(1, 256);
        {
            const uint2 ab = *reinterpret_cast<const uint2*>(&sm.act_pk[g & 3][2 * t]);
            float e[4][4];
#pragma unroll
            for (int i = 0; i < 4; i++) {
                e[i][0] = e[i][1] = e[i][2] = e[i][3] = 0.f;
                mma16816(e[i], a2[i][0], a2[i][1], a2[i][2], a2[i][3], ab.x, ab.y);
            }
            const bool mt = t >= 2;
#pragma unroll
            for (int i = 0; i < 2; i++) {
                const float r0 = mt ? e[2 * i + 1][0] : e[2 * i][0], r1 = mt ? e[2 * i + 1][1] : e[2 * i][1];
                const float r2 = mt ? e[2 * i + 1][2] : e[2 * i][2], r3 = mt ? e[2 * i + 1][3] : e[2 * i][3];
                const int r = 2 * (t & 1) * 32 + 4 * fw + 2 * i + (t >> 1);
                const unsigned long long wa = pk_make(r0, r2, tag), wb = pk_make(r1, r3, tag);
                if (r != bh) pk_store(dst + 2 * i * NFFN * 8, wa); else sm.own2[g] = wa;
                if (r + 32 != bh) pk_store(dst + (2 * i + 32) * NFFN * 8, wb); else sm.own2[g] = wb;
            }
        }
        __syncwarp();
        if (lane == 0) mbar_arrive(smem_u32(&sm.fdone));
        TSTAMPW(9, 8);
        WSTAMP(3);
    } else if (warp == 8) {
        mbar_wait(smem_u32(&sm.hdone), 0);
        uint32_t d0[1], d1[1];
        ll_wait_batch<1>(&gs->hbuf[bh & (HREP - 1)][(4 * lane + 1) & 127][0], 0, tag, tag - 1u, (((4 * lane + 1) & 127) == bh) ? 0 : -1, 0u, 0u, d0, d1);
        if (lane == 0) mbar_arrive(smem_u32(&sm.fdone));
    }
}

}

extern "C" void kernel_launch(void* const* d_in, const int* in_sizes, int n_in, void* d_out, int out_size) {
    (void)in_sizes; (void)n_in; (void)out_size;
    const __nv_bfloat16* x  = (const __nv_bfloat16*)d_in[0];
    const __nv_bfloat16* kc = (const __nv_bfloat16*)d_in[1];
    const __nv_bfloat16* vc = (const __nv_bfloat16*)d_in[2];
    const __nv_bfloat16* wq = (const __nv_bfloat16*)d_in[3];
    const __nv_bfloat16* wo = (const __nv_bfloat16*)d_in[4];
    const __nv_bfloat16* w1 = (const __nv_bfloat16*)d_in[6];
    const __nv_bfloat16* w3 = (const __nv_bfloat16*)d_in[7];
    const __nv_bfloat16* w2 = (const __nv_bfloat16*)d_in[8];
    typedef CUresult (*EncodeFn)(CUtensorMap*, CUtensorMapDataType, cuuint32_t, void*, const cuuint64_t*, const cuuint64_t*,
                                 const cuuint32_t*, const cuuint32_t*, CUtensorMapInterleave, CUtensorMapSwizzle,
                                 CUtensorMapL2promotion, CUtensorMapFloatOOBfill);
    void* fn = nullptr;
    cudaDriverEntryPointQueryResult qres;
    cudaGetDriverEntryPoint("cuTensorMapEncodeTiled", &fn, cudaEnableDefault, &qres);
    EncodeFn encode = (EncodeFn)fn;
    CUtensorMap tmo, tm1, tm3, tm2;
    {
        const cuuint64_t gdim[3] = {64, (cuuint64_t)(kH * kDH), 8};
        const cuuint64_t gstr[2] = {(cuuint64_t)kD * 2, 128};
        const cuuint32_t box[3] = {64, 32, 8};
        const cuuint32_t estr[3] = {1, 1, 1};
        encode(&tmo, CU_TENSOR_MAP_DATA_TYPE_BFLOAT16, 3, (void*)wo, gdim, gstr, box, estr, CU_TENSOR_MAP_INTERLEAVE_NONE,
               CU_TENSOR_MAP_SWIZZLE_128B, CU_TENSOR_MAP_L2_PROMOTION_NONE, CU_TENSOR_MAP_FLOAT_OOB_FILL_NONE);
    }
    {
        const cuuint64_t gdim[3] = {64, (cuuint64_t)kF, 8};
        const cuuint64_t gstr[2] = {(cuuint64_t)kD * 2, 128};
        const cuuint32_t box[3] = {64, 16, 8};
        const cuuint32_t estr[3] = {1, 1, 1};
        encode(&tm2, CU_TENSOR_MAP_DATA_TYPE_BFLOAT16, 3, (void*)w2, gdim, gstr, box, estr, CU_TENSOR_MAP_INTERLEAVE_NONE,
               CU_TENSOR_MAP_SWIZZLE_128B, CU_TENSOR_MAP_L2_PROMOTION_NONE, CU_TENSOR_MAP_FLOAT_OOB_FILL_NONE);
    }
    {
        const cuuint64_t gdim[2] = {(cuuint64_t)kF, (cuuint64_t)kD};
        const cuuint64_t gstr[1] = {(cuuint64_t)kF * 2};
        const cuuint32_t box[2] = {16, 256};
        const cuuint32_t estr[2] = {1, 1};
        encode(&tm1, CU_TENSOR_MAP_DATA_TYPE_BFLOAT16, 2, (void*)w1, gdim, gstr, box, estr, CU_TENSOR_MAP_INTERLEAVE_NONE,
               CU_TENSOR_MAP_SWIZZLE_32B, FFN_PROMO, CU_TENSOR_MAP_FLOAT_OOB_FILL_NONE);
        encode(&tm3, CU_TENSOR_MAP_DATA_TYPE_BFLOAT16, 2, (void*)w3, gdim, gstr, box, estr, CU_TENSOR_MAP_INTERLEAVE_NONE,
               CU_TENSOR_MAP_SWIZZLE_32B, FFN_PROMO, CU_TENSOR_MAP_FLOAT_OOB_FILL_NONE);
    }
    const int smem_bytes = (int)sizeof(Smem) + 1024;
    cudaFuncSetAttribute(fused_decode_kernel, cudaFuncAttributeMaxDynamicSharedMemorySize, smem_bytes);
    void* gs = nullptr;
    cudaGetSymbolAddress(&gs, g_scratch);
    cudaLaunchConfig_t cfg = {};
    cfg.gridDim = dim3(NCTA); cfg.blockDim = dim3(NCT); cfg.dynamicSmemBytes = smem_bytes; cfg.stream = cudaStreamPerThread;
    cudaLaunchAttribute at[1];
    at[0].id = cudaLaunchAttributeCooperative; at[0].val.cooperative = 1;
    cfg.attrs = at; cfg.numAttrs = 1;
    cudaLaunchKernelEx(&cfg, fused_decode_kernel, x, kc, vc, wq, (__nv_bfloat16*)d_out, (Scratch*)gs, tmo, tm1, tm3, tm2);
}
```

```cpp
#include <cuda_runtime.h>
#include <cuda.h>
#include <cuda_bf16.h>
#include <stdint.h>

namespace {

constexpr int kH = 32, kS = 4096, kDH = 128, kD = 512, kF = 1792;
constexpr int NCTA = 128;
constexpr int NFFN = 112;
constexpr int NCW = 16;
constexpr int NCT = NCW * 32;
constexpr int TILE_KEYS = 128;
constexpr int TILE_BYTES = TILE_KEYS * kDH * 2;
constexpr int NSTAGE = 4;
constexpr int NTILE = kS / TILE_KEYS;
constexpr int NWO = 4;
constexpr int JF = NTILE - 1;
constexpr int JP = 20;
constexpr int HREP = 4;
constexpr int OP_PITCH = 80;
constexpr uint32_t SPIN_LIMIT = 1u << 20;
static_assert(NSTAGE == NWO, "ring layout");

struct __align__(1024) Smem {
    uint8_t ring[NSTAGE][TILE_BYTES];
    uint8_t ffn[3][kD * 32];
    float sc[kS];
    float red[8][128];
    float csum[8][32];
    float hst[8][4][2];
    uint32_t x_pk[4][kD / 2];
    uint32_t opart[8][OP_PITCH];
    uint32_t q_pk[kDH / 2];
    float wmax[NCW];
    float wsum[NCW];
    float stat[4][2];
    unsigned long long own1[8];
    unsigned long long own2[8];
    uint32_t hown[8];
    uint32_t act_pk[4][8];
    unsigned long long full[NSTAGE];
    unsigned long long hdone;
    unsigned long long o1bar;
    unsigned long long fdone;
    unsigned long long fbar;
    unsigned long long xbar;
    unsigned long long k0bar;
    uint32_t cnt[NSTAGE];
};
static_assert(sizeof(Smem) + 1024 <= 232448, "smem too large");

struct __align__(128) Scratch {
    unsigned int epoch;
    unsigned int pad0[31];
    unsigned long long hbuf[HREP][NCTA][16];
    unsigned long long qx[NCTA][4][kDH];
    unsigned long long part1[NCTA][kH][8];
    unsigned long long part2[NCTA][NFFN][8];
};
__device__ Scratch g_scratch;

__device__ __forceinline__ uint32_t smem_u32(const void* p) { return (uint32_t)__cvta_generic_to_shared(p); }
__device__ __forceinline__ void mbar_init(uint32_t bar, uint32_t cnt) {
    asm volatile("mbarrier.init.shared::cta.b64 [%0], %1;" ::"r"(bar), "r"(cnt) : "memory");
}
__device__ __forceinline__ void mbar_expect_tx(uint32_t bar, uint32_t bytes) {
    asm volatile("mbarrier.arrive.expect_tx.shared::cta.b64 _, [%0], %1;" ::"r"(bar), "r"(bytes) : "memory");
}
__device__ __forceinline__ void mbar_arrive(uint32_t bar) {
    asm volatile("mbarrier.arrive.shared::cta.b64 _, [%0];" ::"r"(bar) : "memory");
}
__device__ __forceinline__ bool mbar_try(uint32_t bar, uint32_t parity) {
    uint32_t ok;
    asm volatile(
        "{\n.reg .pred p;\n"
        "mbarrier.try_wait.parity.shared::cta.b64 p, [%1], %2;\n"
        "selp.u32 %0, 1, 0, p;\n}"
        : "=r"(ok) : "r"(bar), "r"(parity) : "memory");
    return ok != 0;
}
__device__ __forceinline__ void mbar_wait(uint32_t bar, uint32_t parity) {
    if (mbar_try(bar, parity)) return;
    const uint32_t t0 = clock();
#pragma unroll 1
    while (!mbar_try(bar, parity)) {
        if ((uint32_t)clock() - t0 > (1u << 28)) break;
    }
}
__device__ __forceinline__ void mbar_spin(uint32_t bar, uint32_t parity) {
    const uint32_t t0 = clock();
#pragma unroll 1
    while (true) {
        uint32_t ok;
        asm volatile(
            "{\n.reg .pred p;\n"
            "mbarrier.test_wait.parity.shared::cta.b64 p, [%1], %2;\n"
            "selp.u32 %0, 1, 0, p;\n}"
            : "=r"(ok) : "r"(bar), "r"(parity) : "memory");
        if (ok || (uint32_t)clock() - t0 > (1u << 28)) break;
    }
}
__device__ __forceinline__ void bulk_load(uint32_t dst, const void* src, uint32_t bytes, uint32_t bar, uint64_t pol) {
    asm volatile(
        "cp.async.bulk.shared::cluster.global.mbarrier::complete_tx::bytes.L2::cache_hint [%0], [%1], %2, [%3], %4;"
        ::"r"(dst), "l"(src), "r"(bytes), "r"(bar), "l"(pol) : "memory");
}

__device__ __forceinline__ float bf16r(float v) {
    uint32_t r;
    asm("cvt.rn.bf16x2.f32 %0, %1, %2;" : "=r"(r) : "f"(v), "f"(0.f));
    return __uint_as_float(r);
}
__device__ __forceinline__ uint32_t pack_bf16(float lo, float hi) {
    uint32_t r;
    asm("cvt.rn.bf16x2.f32 %0, %1, %2;" : "=r"(r) : "f"(hi), "f"(lo));
    return r;
}
__device__ __forceinline__ float bf_lo(uint32_t w) { return __uint_as_float(w << 16); }
__device__ __forceinline__ float bf_hi(uint32_t w) { return __uint_as_float(w & 0xffff0000u); }

__device__ __forceinline__ void mma16816(float (&d)[4], uint32_t a0, uint32_t a1, uint32_t a2, uint32_t a3,
                                         uint32_t b0, uint32_t b1) {
    asm volatile(
        "mma.sync.aligned.m16n8k16.row.col.f32.bf16.bf16.f32 {%0,%1,%2,%3}, {%4,%5,%6,%7}, {%8,%9}, {%0,%1,%2,%3};"
        : "+f"(d[0]), "+f"(d[1]), "+f"(d[2]), "+f"(d[3])
        : "r"(a0), "r"(a1), "r"(a2), "r"(a3), "r"(b0), "r"(b1));
}
__device__ __forceinline__ float fast_sqrt(float v) {
    float r;
    asm("sqrt.approx.f32 %0, %1;" : "=f"(r) : "f"(v));
    return r;
}
__device__ __forceinline__ uint4 ldg128(const void* p) {
    uint4 v;
    asm volatile("ld.global.nc.L1::no_allocate.v4.u32 {%0,%1,%2,%3}, [%4];" : "=r"(v.x), "=r"(v.y), "=r"(v.z), "=r"(v.w) : "l"(p));
    return v;
}
__device__ __forceinline__ uint4 lds128(uint32_t a) {
    uint4 v;
    asm volatile("ld.shared.v4.u32 {%0,%1,%2,%3}, [%4];" : "=r"(v.x), "=r"(v.y), "=r"(v.z), "=r"(v.w) : "r"(a));
    return v;
}
__device__ __forceinline__ uint32_t prmt_lo(uint32_t a, uint32_t b) { return __byte_perm(a, b, 0x5410); }
__device__ __forceinline__ uint32_t prmt_hi(uint32_t a, uint32_t b) { return __byte_perm(a, b, 0x7632); }

__device__ __forceinline__ unsigned long long ll_pack(uint32_t d, uint32_t tag) {
    return ((unsigned long long)tag << 32) | d;
}
__device__ __forceinline__ void ll_store1(unsigned long long* p, uint32_t d, uint32_t tag) {
    asm volatile("st.relaxed.gpu.global.b64 [%0], %1;" ::"l"(p), "l"(ll_pack(d, tag)) : "memory");
}
__device__ __forceinline__ void ll_store2(unsigned long long* p, uint32_t d0, uint32_t d1, uint32_t tag) {
    asm volatile("st.relaxed.gpu.global.v2.b64 [%0], {%1, %2};" ::"l"(p), "l"(ll_pack(d0, tag)), "l"(ll_pack(d1, tag))
                 : "memory");
}
template <int N>
__device__ __forceinline__ void ll_wait_batch(const unsigned long long* p, int stride, uint32_t tag, uint32_t have,
                                              int own, uint32_t o0, uint32_t o1, uint32_t (&d0)[N], uint32_t (&d1)[N]) {
    unsigned long long a[N], c[N];
#pragma unroll
    for (int i = 0; i < N; i++) {
        a[i] = (i == own) ? ll_pack(o0, tag) : (unsigned long long)have << 32;
        c[i] = (i == own) ? ll_pack(o1, tag) : (unsigned long long)have << 32;
    }
    uint32_t spins = 0;
#pragma unroll 1
    while (true) {
#pragma unroll
        for (int i = 0; i < N; i++)
            asm volatile(
                "{\n.reg .pred p, q;\n.reg .b32 lo, hi;\n"
                "mov.b64 {lo, hi}, %0;\nsetp.ne.u32 p, hi, %3;\n"
                "mov.b64 {lo, hi}, %1;\nsetp.ne.or.u32 p, hi, %3, p;\n"
                "@p ld.relaxed.gpu.global.v2.b64 {%0, %1}, [%2];\n}"
                : "+l"(a[i]), "+l"(c[i]) : "l"(p + stride * i), "r"(tag) : "memory");
        uint32_t bad = 0;
#pragma unroll
        for (int i = 0; i < N; i++) bad |= ((uint32_t)(a[i] >> 32) ^ tag) | ((uint32_t)(c[i] >> 32) ^ tag);
        if (__all_sync(0xffffffffu, bad == 0) || ++spins > SPIN_LIMIT) break;
    }
#pragma unroll
    for (int i = 0; i < N; i++) { d0[i] = (uint32_t)a[i]; d1[i] = (uint32_t)c[i]; }
}
__device__ __forceinline__ unsigned long long pk_make(float a, float b, uint32_t tag) {
    const uint32_t lo = ((__float_as_uint(a) + 8u) & ~15u) | (tag & 15u);
    const uint32_t hi = ((__float_as_uint(b) + 8u) & ~15u) | ((tag >> 4) & 15u);
    return ((unsigned long long)hi << 32) | lo;
}
__device__ __forceinline__ void pk_store(unsigned long long* p, unsigned long long w) {
    asm volatile("st.relaxed.gpu.global.b64 [%0], %1;" ::"l"(p), "l"(w) : "memory");
}
template <int N>
__device__ __forceinline__ void pk_wait_batch(const unsigned long long* p, int stride, uint32_t tag, int own,
                                              unsigned long long o0, unsigned long long o1, float (&sum)[4]) {
    const unsigned long long want = pk_make(0.f, 0.f, tag) & 0x0000000f0000000full;
    unsigned long long a[N], c[N];
#pragma unroll
    for (int i = 0; i < N; i++) {
        a[i] = (i == own) ? o0 : ~want;
        c[i] = (i == own) ? o1 : ~want;
    }
    uint32_t spins = 0;
#pragma unroll 1
    while (true) {
#pragma unroll
        for (int i = 0; i < N; i++) {
            const unsigned long long x = ((a[i] ^ want) | (c[i] ^ want)) & 0x0000000f0000000full;
            asm volatile("{\n.reg .pred p;\nsetp.ne.u64 p, %3, 0;\n@p ld.relaxed.gpu.global.v2.b64 {%0, %1}, [%2];\n}"
                         : "+l"(a[i]), "+l"(c[i]) : "l"(p + stride * i), "l"(x) : "memory");
        }
        unsigned long long bad = 0;
#pragma unroll
        for (int i = 0; i < N; i++) bad |= (a[i] ^ want) | (c[i] ^ want);
        if (__all_sync(0xffffffffu, (bad & 0x0000000f0000000full) == 0) || ++spins > SPIN_LIMIT) break;
    }
    float s[2][4];
#pragma unroll
    for (int k = 0; k < 4; k++) { s[0][k] = 0.f; s[1][k] = 0.f; }
#pragma unroll
    for (int i = 0; i < N; i++) {
        s[i & 1][0] += __uint_as_float((uint32_t)a[i] & ~15u);
        s[i & 1][1] += __uint_as_float((uint32_t)(a[i] >> 32) & ~15u);
        s[i & 1][2] += __uint_as_float((uint32_t)c[i] & ~15u);
        s[i & 1][3] += __uint_as_float((uint32_t)(c[i] >> 32) & ~15u);
    }
#pragma unroll
    for (int k = 0; k < 4; k++) sum[k] = s[0][k] + s[1][k];
}
__device__ __forceinline__ void ldsm4t(uint32_t (&r)[4], uint32_t a) {
    asm volatile("ldmatrix.sync.aligned.m8n8.x4.trans.shared.b16 {%0,%1,%2,%3}, [%4];"
                 : "=r"(r[0]), "=r"(r[1]), "=r"(r[2]), "=r"(r[3]) : "r"(a));
}
__device__ __forceinline__ void ll_wait1(const unsigned long long* p, uint32_t tag, uint32_t& d) {
    uint32_t spins = 0;
#pragma unroll 1
    while (true) {
        unsigned long long a;
        asm volatile("ld.relaxed.gpu.global.b64 %0, [%1];" : "=l"(a) : "l"(p) : "memory");
        d = (uint32_t)a;
        if ((uint32_t)(a >> 32) == tag || ++spins > SPIN_LIMIT) break;
    }
}
__device__ __forceinline__ uint32_t ln_pair(uint32_t v, uint32_t m2, float rinv) {
    uint32_t d;
    asm("sub.rn.bf16x2 %0, %1, %2;" : "=r"(d) : "r"(v), "r"(m2));
    return pack_bf16(bf_lo(d) * rinv, bf_hi(d) * rinv);
}
__device__ __forceinline__ float warp_sum(float v) {
#pragma unroll
    for (int o = 16; o > 0; o >>= 1) v += __shfl_xor_sync(0xffffffffu, v, o);
    return v;
}
__device__ __forceinline__ float warp_max(float v) {
#pragma unroll
    for (int o = 16; o > 0; o >>= 1) v = fmaxf(v, __shfl_xor_sync(0xffffffffu, v, o));
    return v;
}

__device__ __forceinline__ void bar_sync(int id, int n) { asm volatile("bar.sync %0, %1;" ::"r"(id), "r"(n) : "memory"); }

__global__ void __launch_bounds__(NCT, 1)
fused_decode_kernel(const __nv_bfloat16* __restrict__ x, const __nv_bfloat16* __restrict__ kc,
                    const __nv_bfloat16* __restrict__ vc, const __nv_bfloat16* __restrict__ wq,
                    __nv_bfloat16* __restrict__ out, Scratch* __restrict__ gs,
                    const __grid_constant__ CUtensorMap tmo, const __grid_constant__ CUtensorMap tm1,
                    const __grid_constant__ CUtensorMap tm3, const __grid_constant__ CUtensorMap tm2) {
    extern __shared__ uint8_t smem_raw[];
    Smem& sm = *reinterpret_cast<Smem*>(smem_raw + ((1024u - (smem_u32(smem_raw) & 1023u)) & 1023u));
    const int tid = threadIdx.x, warp = tid >> 5, lane = tid & 31;
    const int bh = blockIdx.x, b = bh >> 5, h = bh & 31;
    const int g = lane >> 2, t = lane & 3;
    const uint8_t* ksrc = reinterpret_cast<const uint8_t*>(kc) + (size_t)bh * (kS * kDH * 2);
    const uint8_t* vsrc = reinterpret_cast<const uint8_t*>(vc) + (size_t)bh * (kS * kDH * 2);
    uint64_t pol;
    asm volatile("createpolicy.fractional.L2::evict_first.b64 %0, 1.0;" : "=l"(pol));

    const int ch = warp & 1, ks = warp >> 1;
    uint4 raw[4];
    {
        const __nv_bfloat16* p = wq + (size_t)(128 * b + 16 * ks + 4 * t) * (kH * kDH) + h * kDH + 64 * ch + 8 * g;
#pragma unroll
        for (int r = 0; r < 4; r++) raw[r] = ldg128(p + (size_t)r * (kH * kDH));
    }
    uint32_t ep;
    asm volatile("ld.relaxed.gpu.global.u32 %0, [%1];" : "=r"(ep) : "l"(&gs->epoch) : "memory");

    if (warp == NCW - 1) {
        if (lane == 0) {
            mbar_init(smem_u32(&sm.xbar), 1);
            mbar_init(smem_u32(&sm.k0bar), 1);
#pragma unroll
            for (int s = 0; s < NSTAGE; s++) {
                mbar_init(smem_u32(&sm.full[s]), 1);
                sm.cnt[s] = 0;
            }
            mbar_init(smem_u32(&sm.hdone), 1);
            mbar_init(smem_u32(&sm.o1bar), 1);
            mbar_init(smem_u32(&sm.fdone), bh < NFFN ? 8 : 1);
            mbar_init(smem_u32(&sm.fbar), 1);
            asm volatile("fence.mbarrier_init.release.cluster;" ::: "memory");
            asm volatile("fence.proxy.async.shared::cta;" ::: "memory");
            mbar_expect_tx(smem_u32(&sm.fbar), 2 * kD * 32 + 16 * kD * 2);
            mbar_expect_tx(smem_u32(&sm.xbar), 4 * kD * 2);
            asm volatile("cp.async.bulk.shared::cluster.global.mbarrier::complete_tx::bytes [%0], [%1], %2, [%3];"
                         ::"r"(smem_u32(sm.x_pk)), "l"(x), "r"(4 * kD * 2), "r"(smem_u32(&sm.xbar)) : "memory");
#pragma unroll 1
            for (int s = 0; s < NWO; s++) {
                mbar_expect_tx(smem_u32(&sm.full[s]), TILE_BYTES);
                asm volatile("cp.async.bulk.tensor.3d.shared::cluster.global.mbarrier::complete_tx::bytes [%0], [%1, {%3, %4, %5}], [%2];"
                             ::"r"(smem_u32(sm.ring[s])), "l"(reinterpret_cast<uint64_t>(&tmo)), "r"(smem_u32(&sm.full[s])),
                               "r"(0), "r"(h * kDH + 32 * s), "r"(0) : "memory");
            }
            mbar_expect_tx(smem_u32(&sm.k0bar), TILE_BYTES);
            bulk_load(smem_u32(sm.ffn), ksrc, TILE_BYTES, smem_u32(&sm.k0bar), pol);
        }
        __syncwarp();
        mbar_wait(smem_u32(&sm.xbar), 0);
        const int row = lane >> 3, l8 = lane & 7;
        float s = 0.f;
        uint4 xv[8];
#pragma unroll
        for (int i = 0; i < 8; i++) {
            xv[i] = lds128(smem_u32(sm.x_pk[row]) + (8 * i + l8) * 16);
            s += ((bf_lo(xv[i].x) + bf_hi(xv[i].x)) + (bf_lo(xv[i].y) + bf_hi(xv[i].y))) +
                 ((bf_lo(xv[i].z) + bf_hi(xv[i].z)) + (bf_lo(xv[i].w) + bf_hi(xv[i].w)));
        }
#pragma unroll
        for (int o = 1; o < 8; o <<= 1) s += __shfl_xor_sync(0xffffffffu, s, o);
        const float mean = s * (1.f / kD);
        float q0 = 0.f, q1 = 0.f;
#pragma unroll
        for (int i = 0; i < 8; i++) {
            const uint32_t w[4] = {xv[i].x, xv[i].y, xv[i].z, xv[i].w};
#pragma unroll
            for (int k = 0; k < 4; k++) {
                const float e0 = bf_lo(w[k]) - mean, e1 = bf_hi(w[k]) - mean;
                q0 = fmaf(e0, e0, q0); q1 = fmaf(e1, e1, q1);
            }
        }
        float s2 = q0 + q1;
#pragma unroll
        for (int o = 1; o < 8; o <<= 1) s2 += __shfl_xor_sync(0xffffffffu, s2, o);
        const float sd = bf16r(fast_sqrt(bf16r(bf16r(s2 * (1.f / kD)) + 1e-5f)));
        if (l8 == 0) {
            sm.stat[row][0] = __uint_as_float(pack_bf16(mean, mean));
            sm.stat[row][1] = __fdividef(1.f, sd);
        }
    }
    __syncthreads();
    const uint32_t tag = ep + 1u;
    {
        const float2 st = *reinterpret_cast<const float2*>(&sm.stat[g & 3][0]);
        const uint2 xw = *reinterpret_cast<const uint2*>(&sm.x_pk[g & 3][64 * b + 8 * ks + 2 * t]);
        const uint32_t b0 = ln_pair(xw.x, __float_as_uint(st.x), st.y);
        const uint32_t b1 = ln_pair(xw.y, __float_as_uint(st.x), st.y);
        float d[4][4];
        const uint32_t* r0 = reinterpret_cast<const uint32_t*>(&raw[0]);
        const uint32_t* r1 = reinterpret_cast<const uint32_t*>(&raw[1]);
        const uint32_t* r2 = reinterpret_cast<const uint32_t*>(&raw[2]);
        const uint32_t* r3 = reinterpret_cast<const uint32_t*>(&raw[3]);
#pragma unroll
        for (int i = 0; i < 4; i++) {
            d[i][0] = d[i][1] = d[i][2] = d[i][3] = 0.f;
            mma16816(d[i], prmt_lo(r0[i], r1[i]), prmt_hi(r0[i], r1[i]), prmt_lo(r2[i], r3[i]), prmt_hi(r2[i], r3[i]), b0, b1);
        }
        float* qp = sm.sc + (ks * 4 + 2 * (t & 1)) * kDH + 64 * ch + 8 * g + 4 * (t >> 1);
        const bool hi = t >= 2;
        *reinterpret_cast<float4*>(qp) = hi ? make_float4(d[2][0], d[2][2], d[3][0], d[3][2])
                                            : make_float4(d[0][0], d[0][2], d[1][0], d[1][2]);
        *reinterpret_cast<float4*>(qp + kDH) = hi ? make_float4(d[2][1], d[2][3], d[3][1], d[3][3])
                                                  : make_float4(d[0][1], d[0][3], d[1][1], d[1][3]);
    }
    __syncthreads();
    {
        float a = 0.f;
#pragma unroll
        for (int k = 0; k < 8; k++) a += sm.sc[k * 512 + tid];
        if ((tid >> 7) != b) ll_store1(&gs->qx[(tid >> 7) * 32 + h][b][tid & 127], __float_as_uint(a), tag);
        else sm.red[b][tid & 127] = a;
    }

    auto release_slot = [&](int slot, int nx) {
        __syncwarp();
        if (lane == 0) {
            uint32_t old;
            asm volatile("atom.acq_rel.cta.shared::cta.inc.u32 %0, [%1], %2;"
                         : "=r"(old) : "r"(smem_u32(&sm.cnt[slot])), "n"(NCW - 1) : "memory");
            if (old == NCW - 1) {
                const uint32_t bar = smem_u32(&sm.full[slot]);
                mbar_expect_tx(bar, TILE_BYTES);
                const uint8_t* src = (nx < NTILE) ? ksrc + (size_t)nx * TILE_BYTES : vsrc + (size_t)(nx - NTILE) * TILE_BYTES;
                bulk_load(smem_u32(sm.ring[slot]), src, TILE_BYTES, bar, pol);
            }
        }
    };

    const uint32_t ldsm_row = (lane & 7) + ((lane >> 4) << 3);
    const uint32_t ldsm_col = ((lane >> 3) & 1) * 8;
    uint32_t wf[8][2][4];
#pragma unroll
    for (int T = 0; T < NWO; T++) {
        mbar_wait(smem_u32(&sm.full[T]), 0);
        const uint32_t base = smem_u32(sm.ring[T]) + (warp >> 1) * 4096 + ldsm_row * 128;
        const uint32_t c0 = 4 * (warp & 1) + (ldsm_col >> 3), sw = lane & 7;
        ldsm4t(wf[2 * T][0], base + ((c0 ^ sw) << 4));
        ldsm4t(wf[2 * T][1], base + (((c0 + 2) ^ sw) << 4));
        ldsm4t(wf[2 * T + 1][0], base + 16 * 128 + ((c0 ^ sw) << 4));
        ldsm4t(wf[2 * T + 1][1], base + 16 * 128 + (((c0 + 2) ^ sw) << 4));
        release_slot(T, T + 1);
    }
    if ((tid >> 7) != b) {
        uint32_t d;
        ll_wait1(&gs->qx[bh][tid >> 7][tid & 127], tag, d);
        sm.red[tid >> 7][tid & 127] = __uint_as_float(d);
    }
    __syncthreads();
    if (tid < kDH) {
        float qv = (sm.red[0][tid] + sm.red[1][tid]) + (sm.red[2][tid] + sm.red[3][tid]);
        reinterpret_cast<__nv_bfloat16*>(sm.q_pk)[tid] = __float2bfloat16_rn(qv);
    }
    __syncthreads();

    int slot = 0; uint32_t ph = 1;
    const bool is_ffn = bh < NFFN;

    float lmax = -INFINITY;
    {
        uint4 qf[4];
#pragma unroll
        for (int i = 0; i < 4; i++) qf[i] = lds128(smem_u32(sm.q_pk) + (t + 4 * (i ^ (g & 1))) * 16);
        const uint32_t lane_off = (8 * warp + g) * 256 + t * 16;
#pragma unroll 1
        for (int j = 0; j < NTILE; j++) {
            mbar_wait(j ? smem_u32(&sm.full[slot]) : smem_u32(&sm.k0bar), j ? ph : 0u);
            const uint32_t base = (j ? smem_u32(sm.ring[slot]) : smem_u32(sm.ffn)) + lane_off;
            float d0[4] = {0.f, 0.f, 0.f, 0.f}, d1[4] = {0.f, 0.f, 0.f, 0.f};
            uint4 va[4];
#pragma unroll
            for (int i = 0; i < 4; i++) va[i] = lds128(base + 64 * (i ^ (g & 1)));
#pragma unroll
            for (int i = 0; i < 4; i++) {
                mma16816(d0, va[i].x, va[i].x, va[i].y, va[i].y, qf[i].x, qf[i].y);
                mma16816(d1, va[i].z, va[i].z, va[i].w, va[i].w, qf[i].z, qf[i].w);
            }
            if (j) release_slot(slot, j + NSTAGE);
            float sv = (g & 1) ? d0[1] + d1[1] : d0[0] + d1[0];
            sv = bf16r(bf16r(sv) * 0.08838834764831845f);
            lmax = fmaxf(lmax, sv);
            if (t == 0) sm.sc[j * TILE_KEYS + 8 * warp + g] = sv;
            if (j && ++slot == NSTAGE) { slot = 0; ph ^= 1; }
        }
    }

    {
        lmax = warp_max(lmax);
        if (lane == 0) sm.wmax[warp] = lmax;
        __syncthreads();
        float gmax = sm.wmax[0];
#pragma unroll
        for (int i = 1; i < NCW; i++) gmax = fmaxf(gmax, sm.wmax[i]);
        float4 a = *reinterpret_cast<float4*>(&sm.sc[tid * 4]);
        float4 c = *reinterpret_cast<float4*>(&sm.sc[2048 + tid * 4]);
        a.x = __expf(a.x - gmax); a.y = __expf(a.y - gmax); a.z = __expf(a.z - gmax); a.w = __expf(a.w - gmax);
        c.x = __expf(c.x - gmax); c.y = __expf(c.y - gmax); c.z = __expf(c.z - gmax); c.w = __expf(c.w - gmax);
        float ls = ((a.x + a.y) + (a.z + a.w)) + ((c.x + c.y) + (c.z + c.w));
        ls = warp_sum(ls);
        if (lane == 0) sm.wsum[warp] = ls;
        __syncthreads();
        float tot = 0.f;
#pragma unroll
        for (int i = 0; i < NCW; i++) tot += sm.wsum[i];
        const float inv = __fdividef(1.f, tot);
        a.x = bf16r(a.x * inv); a.y = bf16r(a.y * inv); a.z = bf16r(a.z * inv); a.w = bf16r(a.w * inv);
        c.x = bf16r(c.x * inv); c.y = bf16r(c.y * inv); c.z = bf16r(c.z * inv); c.w = bf16r(c.w * inv);
        *reinterpret_cast<float4*>(&sm.sc[tid * 4]) = a;
        *reinterpret_cast<float4*>(&sm.sc[2048 + tid * 4]) = c;
        __syncthreads();
    }

    const uint32_t w1s = smem_u32(sm.ffn[0]), w3s = smem_u32(sm.ffn[1]), w2s = smem_u32(sm.ffn[2]);
    auto stage_ffn = [&]() {
        if (!is_ffn || lane != 0) return;
        const int f0 = bh * 16;
        const uint32_t bar = smem_u32(&sm.fbar);
        if (warp >= 2 && warp < 6) {
            const int c = warp - 2;
            const uint32_t dst = ((c & 1) ? w3s : w1s) + (c >> 1) * (256 * 32);
            const uint64_t tm = reinterpret_cast<uint64_t>((c & 1) ? &tm3 : &tm1);
            asm volatile("cp.async.bulk.tensor.2d.shared::cluster.global.mbarrier::complete_tx::bytes [%0], [%1, {%3, %4}], [%2];"
                         ::"r"(dst), "l"(tm), "r"(bar), "r"(f0), "r"((c >> 1) * 256) : "memory");
        } else if (warp == 7) {
            asm volatile("cp.async.bulk.tensor.3d.shared::cluster.global.mbarrier::complete_tx::bytes [%0], [%1, {%3, %4, %5}], [%2];"
                         ::"r"(w2s), "l"(reinterpret_cast<uint64_t>(&tm2)), "r"(bar), "r"(0), "r"(f0), "r"(0) : "memory");
        }
    };
    {
        float acc[8];
#pragma unroll
        for (int i = 0; i < 8; i++) acc[i] = 0.f;
        const int dh = warp & 1, kg = warp >> 1, ks4 = lane >> 3, c8 = lane & 7;
        const uint32_t lane_off = (16 * kg + 4 * ks4) * 256 + 128 * dh + 16 * c8;
#pragma unroll 1
        for (int jv = 0; jv < NTILE; jv++) {
            const float4 pw = *reinterpret_cast<const float4*>(&sm.sc[jv * TILE_KEYS + 16 * kg + 4 * ks4]);
            mbar_wait(smem_u32(&sm.full[slot]), ph);
            const uint32_t base = smem_u32(sm.ring[slot]) + lane_off;
            uint4 v[4];
#pragma unroll
            for (int i = 0; i < 4; i++) v[i] = lds128(base + i * 256);
            const float pv[4] = {pw.x, pw.y, pw.z, pw.w};
#pragma unroll
            for (int i = 0; i < 4; i++) {
                acc[0] = fmaf(pv[i], bf_lo(v[i].x), acc[0]);
                acc[1] = fmaf(pv[i], bf_hi(v[i].x), acc[1]);
                acc[2] = fmaf(pv[i], bf_lo(v[i].y), acc[2]);
                acc[3] = fmaf(pv[i], bf_hi(v[i].y), acc[3]);
                acc[4] = fmaf(pv[i], bf_lo(v[i].z), acc[4]);
                acc[5] = fmaf(pv[i], bf_hi(v[i].z), acc[5]);
                acc[6] = fmaf(pv[i], bf_lo(v[i].w), acc[6]);
                acc[7] = fmaf(pv[i], bf_hi(v[i].w), acc[7]);
            }
            if (jv < NTILE - NSTAGE) release_slot(slot, NTILE + jv + NSTAGE);
            if (jv == JF) { stage_ffn(); __syncwarp(); }
            if (jv == JP) {
                const unsigned long long stale = pk_make(0.f, 0.f, tag - 1u);
                if (t < 2) pk_store(&gs->part1[b * 32 + 2 * warp + t][h][g], stale);
                if (warp == 0 && lane < 4 * HREP) ll_store2(&gs->hbuf[lane >> 2][bh][2 * (lane & 3)], 0u, 0u, tag - 1u);
                if (is_ffn && warp >= 8) {
#pragma unroll
                    for (int i = 0; i < 2; i++) {
                        unsigned long long* dst = &gs->part2[2 * (t & 1) * 32 + 4 * (warp - 8) + 2 * i + (t >> 1)][bh][g];
                        pk_store(dst, stale);
                        pk_store(dst + 32 * NFFN * 8, stale);
                    }
                }
            }
            if (++slot == NSTAGE) { slot = 0; ph ^= 1; }
        }
        const bool up = lane & 16, mid = lane & 8;
        float r[4];
#pragma unroll
        for (int i = 0; i < 4; i++) {
            const float send = up ? acc[i] : acc[i + 4];
            const float keep = up ? acc[i + 4] : acc[i];
            r[i] = keep + __shfl_xor_sync(0xffffffffu, send, 16);
        }
        const float s0 = (mid ? r[2] : r[0]) + __shfl_xor_sync(0xffffffffu, mid ? r[0] : r[2], 8);
        const float s1 = (mid ? r[3] : r[1]) + __shfl_xor_sync(0xffffffffu, mid ? r[1] : r[3], 8);
        const int ksd = 4 * dh + (c8 >> 1);
        sm.opart[kg][16 * (ksd >> 1) + 4 * ks4 + 2 * (ksd & 1) + (c8 & 1)] = pack_bf16(s0, s1);
        __syncthreads();
    }

    {
        float d[4][4];
#pragma unroll
        for (int i = 0; i < 4; i++) { d[i][0] = d[i][1] = d[i][2] = d[i][3] = 0.f; }
#pragma unroll
        for (int i = 0; i < 4; i++) {
            const uint4 bw = lds128(smem_u32(&sm.opart[g][16 * i + 4 * t]));
            mma16816(d[0], wf[2 * i][0][0], wf[2 * i][0][1], wf[2 * i][0][2], wf[2 * i][0][3], bw.x, bw.y);
            mma16816(d[1], wf[2 * i][1][0], wf[2 * i][1][1], wf[2 * i][1][2], wf[2 * i][1][3], bw.x, bw.y);
            mma16816(d[2], wf[2 * i + 1][0][0], wf[2 * i + 1][0][1], wf[2 * i + 1][0][2], wf[2 * i + 1][0][3], bw.z, bw.w);
            mma16816(d[3], wf[2 * i + 1][1][0], wf[2 * i + 1][1][1], wf[2 * i + 1][1][2], wf[2 * i + 1][1][3], bw.z, bw.w);
        }
        const float a0 = (d[0][0] + d[2][0]) + (d[0][1] + d[2][1]), b0 = (d[0][2] + d[2][2]) + (d[0][3] + d[2][3]);
        const float a1 = (d[1][0] + d[3][0]) + (d[1][1] + d[3][1]), b1 = (d[1][2] + d[3][2]) + (d[1][3] + d[3][3]);
        const bool odd = t & 1;
        float ya = (odd ? a1 : a0) + __shfl_xor_sync(0xffffffffu, odd ? a0 : a1, 1);
        float yb = (odd ? b1 : b0) + __shfl_xor_sync(0xffffffffu, odd ? b0 : b1, 1);
        ya += __shfl_xor_sync(0xffffffffu, ya, 2);
        yb += __shfl_xor_sync(0xffffffffu, yb, 2);
        const unsigned long long w = pk_make(ya, yb, tag);
        if (warp == (h >> 1)) {
            if (t == (h & 1)) sm.own1[g] = w;
            __syncwarp();
            if (lane == 0) mbar_arrive(smem_u32(&sm.o1bar));
        }
        if (t < 2 && 2 * warp + t != h) pk_store(&gs->part1[b * 32 + 2 * warp + t][h][g], w);
    }

    if (warp < 2) {
        if (warp == 0) {
            const int q4 = lane & 3, sg = lane >> 2;
            const unsigned long long* src = &gs->part1[bh][sg][2 * q4];
            const uint32_t xA = sm.x_pk[b][8 * h + q4], xB = sm.x_pk[b][8 * h + q4 + 4];
            unsigned long long* dst = &gs->hbuf[sg & (HREP - 1)][bh][2 * q4];
            mbar_spin(smem_u32(&sm.o1bar), 0);
            const ulonglong2 mine = *reinterpret_cast<const ulonglong2*>(&sm.own1[2 * q4]);
            float v[4];
            pk_wait_batch<4>(src, 64, tag, ((h & 7) == sg) ? (h >> 3) : -1, mine.x, mine.y, v);
#pragma unroll
            for (int o = 4; o <= 16; o <<= 1)
#pragma unroll
                for (int k = 0; k < 4; k++) v[k] += __shfl_xor_sync(0xffffffffu, v[k], o);
            const uint32_t wA = pack_bf16(bf_lo(xA) + bf16r(v[0]), bf_hi(xA) + bf16r(v[2]));
            const uint32_t wB = pack_bf16(bf_lo(xB) + bf16r(v[1]), bf_hi(xB) + bf16r(v[3]));
            if (lane < 4 * HREP) ll_store2(dst, wA, wB, tag);
            if (lane < 4) *reinterpret_cast<uint2*>(&sm.hown[2 * q4]) = make_uint2(wA, wB);
            __syncwarp();
            if (lane == 0) mbar_arrive(smem_u32(&sm.hdone));
        }
        {
            const int q4 = 2 * warp + (lane & 1), sg = lane >> 1;
            const unsigned long long* src = &gs->part2[bh][sg][2 * q4];
            uint32_t* op = reinterpret_cast<uint32_t*>(out + b * kD + 16 * h + 2 * q4 + ((lane & 2) ? 8 : 0));
            mbar_wait(smem_u32(&sm.fdone), 0);
            const uint32_t hw = sm.hown[2 * q4 + ((lane >> 1) & 1)];
            const ulonglong2 mine = *reinterpret_cast<const ulonglong2*>(&sm.own2[2 * q4]);
            float v[4];
            pk_wait_batch<7>(src, 128, tag, (is_ffn && (bh & 15) == sg) ? (bh >> 4) : -1, mine.x, mine.y, v);
#pragma unroll
            for (int o = 2; o <= 16; o <<= 1)
#pragma unroll
                for (int k = 0; k < 4; k++) v[k] += __shfl_xor_sync(0xffffffffu, v[k], o);
            const float f0 = (lane & 2) ? v[1] : v[0], f1 = (lane & 2) ? v[3] : v[2];
            if (lane < 4) *op = pack_bf16(bf_lo(hw) + bf16r(f0), bf_hi(hw) + bf16r(f1));
            if (bh == 0 && tid == 0) *reinterpret_cast<volatile unsigned int*>(&gs->epoch) = tag;
        }
    } else if (warp >= 8 && is_ffn) {
        const int fw = warp - 8, u = tid - 256;
        const unsigned long long* src = &gs->hbuf[bh & (HREP - 1)][(g & 3) * 32 + 4 * fw][2 * t];
        unsigned long long* dst = &gs->part2[2 * (t & 1) * 32 + 4 * fw + (t >> 1)][bh][g];
        mbar_wait(smem_u32(&sm.fbar), 0);
        uint32_t a1[4][4], a3[4][4], a2[4][4];
#pragma unroll
        for (int i = 0; i < 4; i++) {
            const uint32_t off = (64 * fw + 16 * i + ldsm_row) * 32 + ((((lane >> 3) ^ (lane >> 2)) & 1) << 4);
            ldsm4t(a1[i], w1s + off);
            ldsm4t(a3[i], w3s + off);
            ldsm4t(a2[i], w2s + fw * 2048 + ldsm_row * 128 + (((2 * i + ((lane >> 3) & 1)) ^ (lane & 7)) << 4));
        }
        uint32_t bw[8];
        mbar_wait(smem_u32(&sm.hdone), 0);
        {
            uint32_t e0[4], e1[4];
            const uint2 mine = *reinterpret_cast<const uint2*>(&sm.hown[2 * t]);
            ll_wait_batch<4>(src, 16, tag, (g < 4) ? tag - 1u : tag, (g == b) ? h - 4 * fw : -1, mine.x, mine.y, e0, e1);
            const uint32_t fill = (g == 4) ? 0x3f803f80u : 0u;
#pragma unroll
            for (int i = 0; i < 4; i++) { bw[2 * i] = (g < 4) ? e0[i] : fill; bw[2 * i + 1] = (g < 4) ? e1[i] : fill; }
        }
        float dg[2][4], du[2][4];
#pragma unroll
        for (int i = 0; i < 2; i++) { dg[i][0] = dg[i][1] = dg[i][2] = dg[i][3] = 0.f; du[i][0] = du[i][1] = du[i][2] = du[i][3] = 0.f; }
#pragma unroll
        for (int i = 0; i < 4; i++) {
            mma16816(dg[i & 1], a1[i][0], a1[i][1], a1[i][2], a1[i][3], bw[2 * i], bw[2 * i + 1]);
            mma16816(du[i & 1], a3[i][0], a3[i][1], a3[i][2], a3[i][3], bw[2 * i], bw[2 * i + 1]);
        }
        {
            float p1[4], p2[4];
#pragma unroll
            for (int i = 0; i < 4; i++) {
                const float l0 = bf_lo(bw[2 * i]), h0 = bf_hi(bw[2 * i]), l1 = bf_lo(bw[2 * i + 1]), h1 = bf_hi(bw[2 * i + 1]);
                p1[i] = (l0 + h0) + (l1 + h1);
                p2[i] = fmaf(l0, l0, h0 * h0) + fmaf(l1, l1, h1 * h1);
            }
            float s1 = (p1[0] + p1[1]) + (p1[2] + p1[3]), s2 = (p2[0] + p2[1]) + (p2[2] + p2[3]);
            s1 += __shfl_xor_sync(0xffffffffu, s1, 1); s2 += __shfl_xor_sync(0xffffffffu, s2, 1);
            s1 += __shfl_xor_sync(0xffffffffu, s1, 2); s2 += __shfl_xor_sync(0xffffffffu, s2, 2);
            if (t == 0 && g < 4) *reinterpret_cast<float2*>(&sm.hst[fw][g][0]) = make_float2(s1, s2);
        }
        if (t < 2) {
            float* dq = &sm.red[fw][(g * 2 + t) * 8];
            *reinterpret_cast<float4*>(dq) = make_float4(dg[0][0] + dg[1][0], dg[0][1] + dg[1][1], dg[0][2] + dg[1][2], dg[0][3] + dg[1][3]);
            *reinterpret_cast<float4*>(dq + 4) = make_float4(du[0][0] + du[1][0], du[0][1] + du[1][1], du[0][2] + du[1][2], du[0][3] + du[1][3]);
        } else if (t == 2) {
            *reinterpret_cast<float4*>(&sm.csum[fw][4 * g]) =
                make_float4(dg[0][0] + dg[1][0], dg[0][2] + dg[1][2], du[0][0] + du[1][0], du[0][2] + du[1][2]);
        }
        bar_sync(1, 256);
        if (u < 128) {
            const int bt = 2 * ((u >> 3) & 1) + (u & 1);
            const int ci = 4 * (u >> 4) + ((u >> 1) & 3);
            float S[2] = {0.f, 0.f}, C[2] = {0.f, 0.f}, s1[2] = {0.f, 0.f}, s2[2] = {0.f, 0.f};
#pragma unroll
            for (int w = 0; w < 8; w++) {
                S[w & 1] += sm.red[w][u];
                C[w & 1] += sm.csum[w][ci];
                const float2 st = *reinterpret_cast<const float2*>(&sm.hst[w][bt][0]);
                s1[w & 1] += st.x; s2[w & 1] += st.y;
            }
            const float mean = (s1[0] + s1[1]) * (1.f / kD);
            const float var = fmaxf(fmaf(-mean, mean, (s2[0] + s2[1]) * (1.f / kD)), 0.f);
            const float sd = bf16r(fast_sqrt(bf16r(bf16r(var) + 1e-5f)));
            const float val = bf16r(__fdividef(fmaf(-bf16r(mean), C[0] + C[1], S[0] + S[1]), sd));
            const float other = __shfl_xor_sync(0xffffffffu, val, 4);
            const float sl = bf16r(__fdividef(val, 1.f + __expf(-val)));
            const float act = sl * other;
            const int f = (u >> 4) + 8 * ((u >> 1) & 1);
            const int wpos = 2 * ((f >> 1) & 3) + (f >> 3);
            if (!(u & 4)) reinterpret_cast<__nv_bfloat16*>(sm.act_pk[bt])[2 * wpos + (f & 1)] = __float2bfloat16_rn(act);
        }
        bar_sync(1, 256);
        {
            const uint2 ab = *reinterpret_cast<const uint2*>(&sm.act_pk[g & 3][2 * t]);
            float e[4][4];
#pragma unroll
            for (int i = 0; i < 4; i++) {
                e[i][0] = e[i][1] = e[i][2] = e[i][3] = 0.f;
                mma16816(e[i], a2[i][0], a2[i][1], a2[i][2], a2[i][3], ab.x, ab.y);
            }
            const bool mt = t >= 2;
#pragma unroll
            for (int i = 0; i < 2; i++) {
                const float r0 = mt ? e[2 * i + 1][0] : e[2 * i][0], r1 = mt ? e[2 * i + 1][1] : e[2 * i][1];
                const float r2 = mt ? e[2 * i + 1][2] : e[2 * i][2], r3 = mt ? e[2 * i + 1][3] : e[2 * i][3];
                const int r = 2 * (t & 1) * 32 + 4 * fw + 2 * i + (t >> 1);
                const unsigned long long wa = pk_make(r0, r2, tag), wb = pk_make(r1, r3, tag);
                if (r != bh) pk_store(dst + 2 * i * NFFN * 8, wa); else sm.own2[g] = wa;
                if (r + 32 != bh) pk_store(dst + (2 * i + 32) * NFFN * 8, wb); else sm.own2[g] = wb;
            }
        }
        __syncwarp();
        if (lane == 0) mbar_arrive(smem_u32(&sm.fdone));
    } else if (warp == 8) {
        mbar_wait(smem_u32(&sm.hdone), 0);
        uint32_t d0[1], d1[1];
        ll_wait_batch<1>(&gs->hbuf[bh & (HREP - 1)][(4 * lane + 1) & 127][0], 0, tag, tag - 1u, (((4 * lane + 1) & 127) == bh) ? 0 : -1, 0u, 0u, d0, d1);
        if (lane == 0) mbar_arrive(smem_u32(&sm.fdone));
    }
}

}

extern "C" void kernel_launch(void* const* d_in, const int* in_sizes, int n_in, void* d_out, int out_size) {
    (void)in_sizes; (void)n_in; (void)out_size;
    const __nv_bfloat16* x  = (const __nv_bfloat16*)d_in[0];
    const __nv_bfloat16* kc = (const __nv_bfloat16*)d_in[1];
    const __nv_bfloat16* vc = (const __nv_bfloat16*)d_in[2];
    const __nv_bfloat16* wq = (const __nv_bfloat16*)d_in[3];
    const __nv_bfloat16* wo = (const __nv_bfloat16*)d_in[4];
    const __nv_bfloat16* w1 = (const __nv_bfloat16*)d_in[6];
    const __nv_bfloat16* w3 = (const __nv_bfloat16*)d_in[7];
    const __nv_bfloat16* w2 = (const __nv_bfloat16*)d_in[8];
    typedef CUresult (*EncodeFn)(CUtensorMap*, CUtensorMapDataType, cuuint32_t, void*, const cuuint64_t*, const cuuint64_t*,
                                 const cuuint32_t*, const cuuint32_t*, CUtensorMapInterleave, CUtensorMapSwizzle,
                                 CUtensorMapL2promotion, CUtensorMapFloatOOBfill);
    void* fn = nullptr;
    cudaDriverEntryPointQueryResult qres;
    cudaGetDriverEntryPoint("cuTensorMapEncodeTiled", &fn, cudaEnableDefault, &qres);
    EncodeFn encode = (EncodeFn)fn;
    CUtensorMap tmo, tm1, tm3, tm2;
    {
        const cuuint64_t gdim[3] = {64, (cuuint64_t)(kH * kDH), 8};
        const cuuint64_t gstr[2] = {(cuuint64_t)kD * 2, 128};
        const cuuint32_t box[3] = {64, 32, 8};
        const cuuint32_t estr[3] = {1, 1, 1};
        encode(&tmo, CU_TENSOR_MAP_DATA_TYPE_BFLOAT16, 3, (void*)wo, gdim, gstr, box, estr, CU_TENSOR_MAP_INTERLEAVE_NONE,
               CU_TENSOR_MAP_SWIZZLE_128B, CU_TENSOR_MAP_L2_PROMOTION_NONE, CU_TENSOR_MAP_FLOAT_OOB_FILL_NONE);
    }
    {
        const cuuint64_t gdim[3] = {64, (cuuint64_t)kF, 8};
        const cuuint64_t gstr[2] = {(cuuint64_t)kD * 2, 128};
        const cuuint32_t box[3] = {64, 16, 8};
        const cuuint32_t estr[3] = {1, 1, 1};
        encode(&tm2, CU_TENSOR_MAP_DATA_TYPE_BFLOAT16, 3, (void*)w2, gdim, gstr, box, estr, CU_TENSOR_MAP_INTERLEAVE_NONE,
               CU_TENSOR_MAP_SWIZZLE_128B, CU_TENSOR_MAP_L2_PROMOTION_NONE, CU_TENSOR_MAP_FLOAT_OOB_FILL_NONE);
    }
    {
        const cuuint64_t gdim[2] = {(cuuint64_t)kF, (cuuint64_t)kD};
        const cuuint64_t gstr[1] = {(cuuint64_t)kF * 2};
        const cuuint32_t box[2] = {16, 256};
        const cuuint32_t estr[2] = {1, 1};
        encode(&tm1, CU_TENSOR_MAP_DATA_TYPE_BFLOAT16, 2, (void*)w1, gdim, gstr, box, estr, CU_TENSOR_MAP_INTERLEAVE_NONE,
               CU_TENSOR_MAP_SWIZZLE_32B, CU_TENSOR_MAP_L2_PROMOTION_L2_64B, CU_TENSOR_MAP_FLOAT_OOB_FILL_NONE);
        encode(&tm3, CU_TENSOR_MAP_DATA_TYPE_BFLOAT16, 2, (void*)w3, gdim, gstr, box, estr, CU_TENSOR_MAP_INTERLEAVE_NONE,
               CU_TENSOR_MAP_SWIZZLE_32B, CU_TENSOR_MAP_L2_PROMOTION_L2_64B, CU_TENSOR_MAP_FLOAT_OOB_FILL_NONE);
    }
    const int smem_bytes = (int)sizeof(Smem) + 1024;
    cudaFuncSetAttribute(fused_decode_kernel, cudaFuncAttributeMaxDynamicSharedMemorySize, smem_bytes);
    void* gs = nullptr;
    cudaGetSymbolAddress(&gs, g_scratch);
    cudaLaunchConfig_t cfg = {};
    cfg.gridDim = dim3(NCTA); cfg.blockDim = dim3(NCT); cfg.dynamicSmemBytes = smem_bytes; cfg.stream = cudaStreamPerThread;
    cudaLaunchAttribute at[1];
    at[0].id = cudaLaunchAttributeCooperative; at[0].val.cooperative = 1;
    cfg.attrs = at; cfg.numAttrs = 1;
    cudaLaunchKernelEx(&cfg, fused_decode_kernel, x, kc, vc, wq, (__nv_bfloat16*)d_out, (Scratch*)gs, tmo, tm1, tm3, tm2);
}
```
